```python
import torch

def _softmax(x, axis=-1):
    return torch.softmax(x, dim=axis)
def _gelu(x):
    return torch.nn.functional.gelu(x, approximate="tanh")
def _silu(x):
    return torch.nn.functional.silu(x)
def _sigmoid(x):
    return torch.sigmoid(x)
def _layernorm(x, axis=-1, eps=1e-5):
    m = x.mean(dim=axis, keepdim=True)
    v = x.var(dim=axis, keepdim=True, unbiased=False)
    return (x - m) / torch.sqrt(v + eps)
def _scatter_add(tgt, idx, src, axis=0):
    return tgt.clone().index_add_(axis, idx, src)
def _segment_sum(src, seg, n):
    out = torch.zeros((n,) + src.shape[1:], dtype=src.dtype)
    return out.index_add_(0, seg, src)
def _pad(x, pw):
    flat = tuple(v for pair in reversed(pw) for v in pair)
    return torch.nn.functional.pad(x, flat)

kernel_name = 'parallel_sum__linear_attn_block__geglu_ffn__prompt'

def setup_inputs():

    _w = (lambda a: (lambda t: t.to(torch.bfloat16) if t.is_floating_point() else t)(torch.as_tensor(a)))
    def _A_setup():
        B, S, D = 1, 2048, 448
        return {
            "x": _w((lambda *s: torch.randn(*s, dtype=torch.bfloat16) * 0.05)(B, S, D)),
            "wqkv": _w((lambda *s: torch.randn(*s, dtype=torch.bfloat16) * 0.4)(D, 3 * D)),
            "wo": _w((lambda *s: torch.randn(*s, dtype=torch.bfloat16) * 0.2)(D, D)),
        }
    _A_in = _A_setup()

    def _B_setup():
        B, S, D, F = 1, 2048, 448, 1792
        return {
            "x": _w((lambda *s: torch.randn(*s, dtype=torch.bfloat16) * 0.05)(B, S, D)),
            "w_gate": _w((lambda *s: torch.randn(*s, dtype=torch.bfloat16) * 0.05)(D, F)),
            "w_up": _w((lambda *s: torch.randn(*s, dtype=torch.bfloat16) * 0.05)(D, F)),
            "w_down": _w((lambda *s: torch.randn(*s, dtype=torch.bfloat16) * 0.05)(F, D)),
        }
    _B_in = _B_setup()

    return {
        "A_x": _A_in["x"],
        "A_wqkv": _A_in["wqkv"],
        "A_wo": _A_in["wo"],
        "B_x": _B_in["x"],
        "B_w_gate": _B_in["w_gate"],
        "B_w_up": _B_in["w_up"],
        "B_w_down": _B_in["w_down"],
    }

def reference(A_x, A_wqkv, A_wo, B_x, B_w_gate, B_w_up, B_w_down):
    def _A_ref(x, wqkv, wo):
        B, S, D = x.shape
        H = 16; Dh = D // H
        qkv = (lambda x, *d: x.permute(*d))((x @ wqkv).reshape(B, S, 3, H, Dh), 2, 0, 3, 1, 4)
        q, k, v = qkv[0], qkv[1], qkv[2]
        phi = lambda t: torch.where(t > 0, t + 1, torch.exp(t)) + 1e-6
        pq, pk = phi(q), phi(k)
        kv = torch.einsum("bhsd,bhse->bhde", pk, v)
        z = torch.einsum("bhsd->bhd", pk)
        num = torch.einsum("bhqd,bhde->bhqe", pq, kv)
        den = torch.einsum("bhqd,bhd->bhq", pq, z)[..., None] + 1e-6
        o = num / den
        return (lambda x, *d: x.permute(*d))(o, 0, 2, 1, 3).reshape(B, S, D) @ wo

    def _B_ref(x, w_gate, w_up, w_down):
        return (_gelu(x @ w_gate) * (x @ w_up)) @ w_down

    x = A_x
    xn = _layernorm(x, axis=-1)
    return x + _A_ref(xn, A_wqkv, A_wo) + _B_ref(xn, B_w_gate, B_w_up, B_w_down)
```

```cpp
#include <cuda_runtime.h>
#include <cuda.h>
#include <cuda_bf16.h>
#include <stdint.h>

namespace {

constexpr int DM = 448;
constexpr uint32_t SB = 0x400;
constexpr uint32_t OFF_X = 0;
constexpr uint32_t OFF_SLOT = 7 * 16384;
constexpr uint32_t OFF_BAR = 14 * 16384;
constexpr uint32_t BAR_FULL = OFF_BAR;
constexpr uint32_t BAR_EMPTY = OFF_BAR + 512;
constexpr uint32_t BAR_X = OFF_BAR + 1024;
constexpr uint32_t BAR_KVP = OFF_BAR + 1088;
constexpr uint32_t BAR_KVREAD = OFF_BAR + 1104;
constexpr uint32_t BAR_KVB = OFF_BAR + 1112;
constexpr uint32_t OFF_TAG = OFF_BAR + 1120;
constexpr uint32_t SMEM_BYTES = OFF_BAR + 1152;
constexpr uint32_t OFF_KVB = OFF_SLOT + 6 * 16384 + 8192;

__device__ float g_kvsum[2 * 8 * 1792];
__device__ unsigned g_cnt[8 * 32];
__device__ uint4 g_part[128 * 7168];
#define STAMP(i)
#define STAMPW(i)

struct Maps { CUtensorMap x, qkv, q64, g, u, g64, u64, d, d32, o; };

__host__ __device__ constexpr uint32_t buf_off(int t) {
  if (t < 7) return OFF_SLOT + t * 16384;
  if (t < 21) return OFF_SLOT + ((t - 7) % 5) * 16384;
  if (t < 35) { int r = (t - 21) % 6; return OFF_SLOT + (r == 0 ? 5 : (r == 1 ? 4 : r - 2)) * 16384; }
  if (t >= 48) t -= 13;
  int u = t - 35;
  if ((u & 1) == 0) return OFF_X + (u / 2) * 16384;
  int r = u / 2;
  return OFF_SLOT + (r < 4 ? r : (r == 4 ? 5 : 4)) * 16384;
}
__host__ __device__ constexpr int dep_of(int t) {
  if (t < 7) return -1;
  if (t < 12) return t - 7;
  if (t < 21) return t - 5;
  if (t == 21) return -2;
  if (t < 35) return t - 6;
  if (t < 48) return 28 + (t - 35 + 1) / 2;
  return t - 13;
}

__device__ __forceinline__ uint32_t smem_u32(const void* p) { return (uint32_t)__cvta_generic_to_shared(p); }
__device__ __forceinline__ void mbar_init(uint32_t bar, uint32_t cnt) { asm volatile("mbarrier.init.shared::cta.b64 [%0], %1;" :: "r"(bar), "r"(cnt) : "memory"); }
__device__ __forceinline__ void mbar_expect_tx(uint32_t bar, uint32_t bytes) { asm volatile("mbarrier.arrive.expect_tx.shared::cta.b64 _, [%0], %1;" :: "r"(bar), "r"(bytes) : "memory"); }
__device__ __forceinline__ void mbar_arrive(uint32_t bar) { asm volatile("mbarrier.arrive.shared::cta.b64 _, [%0];" :: "r"(bar) : "memory"); }
__device__ __forceinline__ void mbar_arrive_pred(uint32_t bar, uint32_t pred) {
  asm volatile("{\n.reg .pred p;\nsetp.ne.u32 p, %1, 0;\n@p mbarrier.arrive.shared::cta.b64 _, [%0];\n}" :: "r"(bar), "r"(pred) : "memory");
}
__device__ __forceinline__ void mbar_wait(uint32_t bar) {
  asm volatile("{\n.reg .pred P1;\n.reg .u32 cnt;\nmov.u32 cnt, 0;\nLAB_WAIT:\n"
    "mbarrier.try_wait.parity.shared::cta.b64 P1, [%0], 0;\n@P1 bra DONE;\n"
    "add.u32 cnt, cnt, 1;\nsetp.lt.u32 P1, cnt, 4000000;\n@P1 bra LAB_WAIT;\ntrap;\nDONE:\n}\n" :: "r"(bar) : "memory");
}
__device__ __forceinline__ void tma2d(uint32_t dst, const CUtensorMap* m, uint32_t bar, int c0, int c1) {
  asm volatile("cp.async.bulk.tensor.2d.shared::cluster.global.mbarrier::complete_tx::bytes [%0], [%1, {%3, %4}], [%2];"
    :: "r"(dst), "l"(m), "r"(bar), "r"(c0), "r"(c1) : "memory");
}
__device__ __forceinline__ void fence_async() { asm volatile("fence.proxy.async.shared::cta;" ::: "memory"); }
__device__ __forceinline__ void wg_fence() { asm volatile("wgmma.fence.sync.aligned;" ::: "memory"); }
__device__ __forceinline__ void wg_commit() { asm volatile("wgmma.commit_group.sync.aligned;" ::: "memory"); }
template<int N> __device__ __forceinline__ void wg_wait() { asm volatile("wgmma.wait_group.sync.aligned %0;" :: "n"(N) : "memory"); }
__device__ __forceinline__ void wg_bar(int wg) { asm volatile("bar.sync %0, 128;" :: "r"(wg + 1) : "memory"); }
__host__ __device__ constexpr uint64_t make_desc(uint32_t addr, uint32_t lbo, uint32_t sbo, uint64_t swz) {
  return (uint64_t)((addr & 0x3FFFF) >> 4) | ((uint64_t)(lbo >> 4) << 16) | ((uint64_t)(sbo >> 4) << 32) | (swz << 62);
}
template<int LO, int HI, int N> __device__ __forceinline__ void fence_regs(float (&a)[N]) {
  #pragma unroll
  for (int i = LO; i < HI; i++) asm volatile("" : "+f"(a[i]) :: "memory");
}
__device__ __forceinline__ uint32_t pack2(float lo, float hi) { uint32_t r; asm("cvt.rn.bf16x2.f32 %0, %1, %2;" : "=r"(r) : "f"(hi), "f"(lo)); return r; }
__device__ __forceinline__ void ldsm4(uint32_t& a, uint32_t& b, uint32_t& c, uint32_t& d, uint32_t addr) {
  asm volatile("ldmatrix.sync.aligned.m8n8.x4.shared.b16 {%0, %1, %2, %3}, [%4];" : "=r"(a), "=r"(b), "=r"(c), "=r"(d) : "r"(addr) : "memory");
}
__device__ __forceinline__ void stsm4(uint32_t addr, uint32_t a, uint32_t b, uint32_t c, uint32_t d) {
  asm volatile("stmatrix.sync.aligned.m8n8.x4.shared.b16 [%0], {%1, %2, %3, %4};" :: "r"(addr), "r"(a), "r"(b), "r"(c), "r"(d) : "memory");
}
__device__ __forceinline__ void mma_rowsum(float (&c)[4], uint32_t a0, uint32_t a1, uint32_t a2, uint32_t a3) {
  asm volatile("mma.sync.aligned.m16n8k16.row.col.f32.bf16.bf16.f32 {%0,%1,%2,%3}, {%4,%5,%6,%7}, {%8,%8}, {%0,%1,%2,%3};"
    : "+f"(c[0]), "+f"(c[1]), "+f"(c[2]), "+f"(c[3]) : "r"(a0), "r"(a1), "r"(a2), "r"(a3), "r"(0x3F803F80u));
}
__device__ __forceinline__ uint32_t hsub2(uint32_t a, uint32_t b) { uint32_t r; asm("sub.rn.bf16x2 %0, %1, %2;" : "=r"(r) : "r"(a), "r"(b)); return r; }
__device__ __forceinline__ float bf_lo(uint32_t u) { return __uint_as_float(u << 16); }
__device__ __forceinline__ float bf_hi(uint32_t u) { return __uint_as_float(u & 0xFFFF0000u); }
__device__ __forceinline__ float bf_round(float x) { return bf_lo(pack2(x, 0.f)); }
__device__ __forceinline__ float ex2(float x) { float r; asm("ex2.approx.ftz.f32 %0, %1;" : "=f"(r) : "f"(x)); return r; }
__device__ __forceinline__ float rcp(float x) { float r; asm("rcp.approx.ftz.f32 %0, %1;" : "=f"(r) : "f"(x)); return r; }
__device__ __forceinline__ uint32_t phi2(float a0, float a1, float r, float rl) {
  float e0 = ex2(a0 * rl) + 1e-6f, e1 = ex2(a1 * rl) + 1e-6f;
  float p0 = a0 > 0.f ? fmaf(a0, r, 1.000001f) : e0;
  float p1 = a1 > 0.f ? fmaf(a1, r, 1.000001f) : e1;
  return pack2(p0, p1);
}
__device__ __forceinline__ float geglu1(float g, float u, float c0, float c1, float c2) {
  float t = fmaf(g * g, c1, c0) * g, th;
  asm("tanh.approx.f32 %0, %1;" : "=f"(th) : "f"(t));
  float hh = g * u * c2;
  return fmaf(hh, th, hh);
}

template<int SD, uint64_t AD, uint64_t BD, int SZ> __device__ __forceinline__ void wg_ss128(float (&d)[SZ], uint32_t aoff) {
  if constexpr (SD == 0)
  asm volatile("{\n.reg .pred p;\n.reg .b64 ad, bd;\n.reg .b32 lo;\nsetp.ne.b32 p, 0, 0;\n"
    "add.u32 lo, %64, %65;\nmov.b64 ad, {lo, %66};\n"
    "mov.b64 bd, %67;\n"
    "wgmma.mma_async.sync.aligned.m64n128k16.f32.bf16.bf16 "
    "{%0, %1, %2, %3, %4, %5, %6, %7, %8, %9, %10, %11, %12, %13, %14, %15, %16, %17, %18, %19, %20, %21, %22, %23, %24, %25, %26, %27, %28, %29, %30, %31, %32, %33, %34, %35, %36, %37, %38, %39, %40, %41, %42, %43, %44, %45, %46, %47, %48, %49, %50, %51, %52, %53, %54, %55, %56, %57, %58, %59, %60, %61, %62, %63}, "
    "ad, bd, p, 1, 1, 0, 1;\n}\n"
    : "=f"(d[0]), "=f"(d[1]), "=f"(d[2]), "=f"(d[3]), "=f"(d[4]), "=f"(d[5]), "=f"(d[6]), "=f"(d[7]), "=f"(d[8]), "=f"(d[9]), "=f"(d[10]), "=f"(d[11]), "=f"(d[12]), "=f"(d[13]), "=f"(d[14]), "=f"(d[15]), "=f"(d[16]), "=f"(d[17]), "=f"(d[18]), "=f"(d[19]), "=f"(d[20]), "=f"(d[21]), "=f"(d[22]), "=f"(d[23]), "=f"(d[24]), "=f"(d[25]), "=f"(d[26]), "=f"(d[27]), "=f"(d[28]), "=f"(d[29]), "=f"(d[30]), "=f"(d[31]), "=f"(d[32]), "=f"(d[33]), "=f"(d[34]), "=f"(d[35]), "=f"(d[36]), "=f"(d[37]), "=f"(d[38]), "=f"(d[39]), "=f"(d[40]), "=f"(d[41]), "=f"(d[42]), "=f"(d[43]), "=f"(d[44]), "=f"(d[45]), "=f"(d[46]), "=f"(d[47]), "=f"(d[48]), "=f"(d[49]), "=f"(d[50]), "=f"(d[51]), "=f"(d[52]), "=f"(d[53]), "=f"(d[54]), "=f"(d[55]), "=f"(d[56]), "=f"(d[57]), "=f"(d[58]), "=f"(d[59]), "=f"(d[60]), "=f"(d[61]), "=f"(d[62]), "=f"(d[63])
    : "r"(aoff), "n"((uint32_t)AD), "n"((uint32_t)(AD >> 32)), "n"(BD));
  if constexpr (SD == 1)
  asm volatile("{\n.reg .pred p;\n.reg .b64 ad, bd;\n.reg .b32 lo;\nsetp.ne.b32 p, 1, 0;\n"
    "add.u32 lo, %64, %65;\nmov.b64 ad, {lo, %66};\n"
    "mov.b64 bd, %67;\n"
    "wgmma.mma_async.sync.aligned.m64n128k16.f32.bf16.bf16 "
    "{%0, %1, %2, %3, %4, %5, %6, %7, %8, %9, %10, %11, %12, %13, %14, %15, %16, %17, %18, %19, %20, %21, %22, %23, %24, %25, %26, %27, %28, %29, %30, %31, %32, %33, %34, %35, %36, %37, %38, %39, %40, %41, %42, %43, %44, %45, %46, %47, %48, %49, %50, %51, %52, %53, %54, %55, %56, %57, %58, %59, %60, %61, %62, %63}, "
    "ad, bd, p, 1, 1, 0, 1;\n}\n"
    : "+f"(d[0]), "+f"(d[1]), "+f"(d[2]), "+f"(d[3]), "+f"(d[4]), "+f"(d[5]), "+f"(d[6]), "+f"(d[7]), "+f"(d[8]), "+f"(d[9]), "+f"(d[10]), "+f"(d[11]), "+f"(d[12]), "+f"(d[13]), "+f"(d[14]), "+f"(d[15]), "+f"(d[16]), "+f"(d[17]), "+f"(d[18]), "+f"(d[19]), "+f"(d[20]), "+f"(d[21]), "+f"(d[22]), "+f"(d[23]), "+f"(d[24]), "+f"(d[25]), "+f"(d[26]), "+f"(d[27]), "+f"(d[28]), "+f"(d[29]), "+f"(d[30]), "+f"(d[31]), "+f"(d[32]), "+f"(d[33]), "+f"(d[34]), "+f"(d[35]), "+f"(d[36]), "+f"(d[37]), "+f"(d[38]), "+f"(d[39]), "+f"(d[40]), "+f"(d[41]), "+f"(d[42]), "+f"(d[43]), "+f"(d[44]), "+f"(d[45]), "+f"(d[46]), "+f"(d[47]), "+f"(d[48]), "+f"(d[49]), "+f"(d[50]), "+f"(d[51]), "+f"(d[52]), "+f"(d[53]), "+f"(d[54]), "+f"(d[55]), "+f"(d[56]), "+f"(d[57]), "+f"(d[58]), "+f"(d[59]), "+f"(d[60]), "+f"(d[61]), "+f"(d[62]), "+f"(d[63])
    : "r"(aoff), "n"((uint32_t)AD), "n"((uint32_t)(AD >> 32)), "n"(BD));
}
template<int SD, uint64_t AD, uint64_t BD, int SZ> __device__ __forceinline__ void wg_ss120(float (&d)[SZ], uint32_t aoff) {
  if constexpr (SD == 0)
  asm volatile("{\n.reg .pred p;\n.reg .b64 ad, bd;\n.reg .b32 lo;\nsetp.ne.b32 p, 0, 0;\n"
    "add.u32 lo, %60, %61;\nmov.b64 ad, {lo, %62};\n"
    "mov.b64 bd, %63;\n"
    "wgmma.mma_async.sync.aligned.m64n120k16.f32.bf16.bf16 "
    "{%0, %1, %2, %3, %4, %5, %6, %7, %8, %9, %10, %11, %12, %13, %14, %15, %16, %17, %18, %19, %20, %21, %22, %23, %24, %25, %26, %27, %28, %29, %30, %31, %32, %33, %34, %35, %36, %37, %38, %39, %40, %41, %42, %43, %44, %45, %46, %47, %48, %49, %50, %51, %52, %53, %54, %55, %56, %57, %58, %59}, "
    "ad, bd, p, 1, 1, 0, 1;\n}\n"
    : "=f"(d[0]), "=f"(d[1]), "=f"(d[2]), "=f"(d[3]), "=f"(d[4]), "=f"(d[5]), "=f"(d[6]), "=f"(d[7]), "=f"(d[8]), "=f"(d[9]), "=f"(d[10]), "=f"(d[11]), "=f"(d[12]), "=f"(d[13]), "=f"(d[14]), "=f"(d[15]), "=f"(d[16]), "=f"(d[17]), "=f"(d[18]), "=f"(d[19]), "=f"(d[20]), "=f"(d[21]), "=f"(d[22]), "=f"(d[23]), "=f"(d[24]), "=f"(d[25]), "=f"(d[26]), "=f"(d[27]), "=f"(d[28]), "=f"(d[29]), "=f"(d[30]), "=f"(d[31]), "=f"(d[32]), "=f"(d[33]), "=f"(d[34]), "=f"(d[35]), "=f"(d[36]), "=f"(d[37]), "=f"(d[38]), "=f"(d[39]), "=f"(d[40]), "=f"(d[41]), "=f"(d[42]), "=f"(d[43]), "=f"(d[44]), "=f"(d[45]), "=f"(d[46]), "=f"(d[47]), "=f"(d[48]), "=f"(d[49]), "=f"(d[50]), "=f"(d[51]), "=f"(d[52]), "=f"(d[53]), "=f"(d[54]), "=f"(d[55]), "=f"(d[56]), "=f"(d[57]), "=f"(d[58]), "=f"(d[59])
    : "r"(aoff), "n"((uint32_t)AD), "n"((uint32_t)(AD >> 32)), "n"(BD));
  if constexpr (SD == 1)
  asm volatile("{\n.reg .pred p;\n.reg .b64 ad, bd;\n.reg .b32 lo;\nsetp.ne.b32 p, 1, 0;\n"
    "add.u32 lo, %60, %61;\nmov.b64 ad, {lo, %62};\n"
    "mov.b64 bd, %63;\n"
    "wgmma.mma_async.sync.aligned.m64n120k16.f32.bf16.bf16 "
    "{%0, %1, %2, %3, %4, %5, %6, %7, %8, %9, %10, %11, %12, %13, %14, %15, %16, %17, %18, %19, %20, %21, %22, %23, %24, %25, %26, %27, %28, %29, %30, %31, %32, %33, %34, %35, %36, %37, %38, %39, %40, %41, %42, %43, %44, %45, %46, %47, %48, %49, %50, %51, %52, %53, %54, %55, %56, %57, %58, %59}, "
    "ad, bd, p, 1, 1, 0, 1;\n}\n"
    : "+f"(d[0]), "+f"(d[1]), "+f"(d[2]), "+f"(d[3]), "+f"(d[4]), "+f"(d[5]), "+f"(d[6]), "+f"(d[7]), "+f"(d[8]), "+f"(d[9]), "+f"(d[10]), "+f"(d[11]), "+f"(d[12]), "+f"(d[13]), "+f"(d[14]), "+f"(d[15]), "+f"(d[16]), "+f"(d[17]), "+f"(d[18]), "+f"(d[19]), "+f"(d[20]), "+f"(d[21]), "+f"(d[22]), "+f"(d[23]), "+f"(d[24]), "+f"(d[25]), "+f"(d[26]), "+f"(d[27]), "+f"(d[28]), "+f"(d[29]), "+f"(d[30]), "+f"(d[31]), "+f"(d[32]), "+f"(d[33]), "+f"(d[34]), "+f"(d[35]), "+f"(d[36]), "+f"(d[37]), "+f"(d[38]), "+f"(d[39]), "+f"(d[40]), "+f"(d[41]), "+f"(d[42]), "+f"(d[43]), "+f"(d[44]), "+f"(d[45]), "+f"(d[46]), "+f"(d[47]), "+f"(d[48]), "+f"(d[49]), "+f"(d[50]), "+f"(d[51]), "+f"(d[52]), "+f"(d[53]), "+f"(d[54]), "+f"(d[55]), "+f"(d[56]), "+f"(d[57]), "+f"(d[58]), "+f"(d[59])
    : "r"(aoff), "n"((uint32_t)AD), "n"((uint32_t)(AD >> 32)), "n"(BD));
}
template<int SD, uint64_t AD, uint64_t BD, int SZ> __device__ __forceinline__ void wg_ss64t(float (&d)[SZ], uint32_t aoff) {
  if constexpr (SD == 0)
  asm volatile("{\n.reg .pred p;\n.reg .b64 ad, bd;\n.reg .b32 lo;\nsetp.ne.b32 p, 0, 0;\n"
    "add.u32 lo, %32, %33;\nmov.b64 ad, {lo, %34};\n"
    "add.u32 lo, %32, %35;\nmov.b64 bd, {lo, %36};\n"
    "wgmma.mma_async.sync.aligned.m64n64k16.f32.bf16.bf16 "
    "{%0, %1, %2, %3, %4, %5, %6, %7, %8, %9, %10, %11, %12, %13, %14, %15, %16, %17, %18, %19, %20, %21, %22, %23, %24, %25, %26, %27, %28, %29, %30, %31}, "
    "ad, bd, p, 1, 1, 1, 1;\n}\n"
    : "=f"(d[0]), "=f"(d[1]), "=f"(d[2]), "=f"(d[3]), "=f"(d[4]), "=f"(d[5]), "=f"(d[6]), "=f"(d[7]), "=f"(d[8]), "=f"(d[9]), "=f"(d[10]), "=f"(d[11]), "=f"(d[12]), "=f"(d[13]), "=f"(d[14]), "=f"(d[15]), "=f"(d[16]), "=f"(d[17]), "=f"(d[18]), "=f"(d[19]), "=f"(d[20]), "=f"(d[21]), "=f"(d[22]), "=f"(d[23]), "=f"(d[24]), "=f"(d[25]), "=f"(d[26]), "=f"(d[27]), "=f"(d[28]), "=f"(d[29]), "=f"(d[30]), "=f"(d[31])
    : "r"(aoff), "n"((uint32_t)AD), "n"((uint32_t)(AD >> 32)), "n"((uint32_t)BD), "n"((uint32_t)(BD >> 32)));
  if constexpr (SD == 1)
  asm volatile("{\n.reg .pred p;\n.reg .b64 ad, bd;\n.reg .b32 lo;\nsetp.ne.b32 p, 1, 0;\n"
    "add.u32 lo, %32, %33;\nmov.b64 ad, {lo, %34};\n"
    "add.u32 lo, %32, %35;\nmov.b64 bd, {lo, %36};\n"
    "wgmma.mma_async.sync.aligned.m64n64k16.f32.bf16.bf16 "
    "{%0, %1, %2, %3, %4, %5, %6, %7, %8, %9, %10, %11, %12, %13, %14, %15, %16, %17, %18, %19, %20, %21, %22, %23, %24, %25, %26, %27, %28, %29, %30, %31}, "
    "ad, bd, p, 1, 1, 1, 1;\n}\n"
    : "+f"(d[0]), "+f"(d[1]), "+f"(d[2]), "+f"(d[3]), "+f"(d[4]), "+f"(d[5]), "+f"(d[6]), "+f"(d[7]), "+f"(d[8]), "+f"(d[9]), "+f"(d[10]), "+f"(d[11]), "+f"(d[12]), "+f"(d[13]), "+f"(d[14]), "+f"(d[15]), "+f"(d[16]), "+f"(d[17]), "+f"(d[18]), "+f"(d[19]), "+f"(d[20]), "+f"(d[21]), "+f"(d[22]), "+f"(d[23]), "+f"(d[24]), "+f"(d[25]), "+f"(d[26]), "+f"(d[27]), "+f"(d[28]), "+f"(d[29]), "+f"(d[30]), "+f"(d[31])
    : "r"(aoff), "n"((uint32_t)AD), "n"((uint32_t)(AD >> 32)), "n"((uint32_t)BD), "n"((uint32_t)(BD >> 32)));
}
template<int SD, uint64_t BD, int SZ> __device__ __forceinline__ void wg_rs128(float (&d)[SZ], uint32_t a0, uint32_t a1, uint32_t a2, uint32_t a3) {
  if constexpr (SD == 0)
  asm volatile("{\n.reg .pred p;\n.reg .b64 ad, bd;\n.reg .b32 lo;\nsetp.ne.b32 p, 0, 0;\n"
    "mov.b64 bd, %68;\n"
    "wgmma.mma_async.sync.aligned.m64n128k16.f32.bf16.bf16 "
    "{%0, %1, %2, %3, %4, %5, %6, %7, %8, %9, %10, %11, %12, %13, %14, %15, %16, %17, %18, %19, %20, %21, %22, %23, %24, %25, %26, %27, %28, %29, %30, %31, %32, %33, %34, %35, %36, %37, %38, %39, %40, %41, %42, %43, %44, %45, %46, %47, %48, %49, %50, %51, %52, %53, %54, %55, %56, %57, %58, %59, %60, %61, %62, %63}, "
    "{%64, %65, %66, %67}, bd, p, 1, 1, 1;\n}\n"
    : "=f"(d[0]), "=f"(d[1]), "=f"(d[2]), "=f"(d[3]), "=f"(d[4]), "=f"(d[5]), "=f"(d[6]), "=f"(d[7]), "=f"(d[8]), "=f"(d[9]), "=f"(d[10]), "=f"(d[11]), "=f"(d[12]), "=f"(d[13]), "=f"(d[14]), "=f"(d[15]), "=f"(d[16]), "=f"(d[17]), "=f"(d[18]), "=f"(d[19]), "=f"(d[20]), "=f"(d[21]), "=f"(d[22]), "=f"(d[23]), "=f"(d[24]), "=f"(d[25]), "=f"(d[26]), "=f"(d[27]), "=f"(d[28]), "=f"(d[29]), "=f"(d[30]), "=f"(d[31]), "=f"(d[32]), "=f"(d[33]), "=f"(d[34]), "=f"(d[35]), "=f"(d[36]), "=f"(d[37]), "=f"(d[38]), "=f"(d[39]), "=f"(d[40]), "=f"(d[41]), "=f"(d[42]), "=f"(d[43]), "=f"(d[44]), "=f"(d[45]), "=f"(d[46]), "=f"(d[47]), "=f"(d[48]), "=f"(d[49]), "=f"(d[50]), "=f"(d[51]), "=f"(d[52]), "=f"(d[53]), "=f"(d[54]), "=f"(d[55]), "=f"(d[56]), "=f"(d[57]), "=f"(d[58]), "=f"(d[59]), "=f"(d[60]), "=f"(d[61]), "=f"(d[62]), "=f"(d[63])
    : "r"(a0), "r"(a1), "r"(a2), "r"(a3), "n"(BD));
  if constexpr (SD == 1)
  asm volatile("{\n.reg .pred p;\n.reg .b64 ad, bd;\n.reg .b32 lo;\nsetp.ne.b32 p, 1, 0;\n"
    "mov.b64 bd, %68;\n"
    "wgmma.mma_async.sync.aligned.m64n128k16.f32.bf16.bf16 "
    "{%0, %1, %2, %3, %4, %5, %6, %7, %8, %9, %10, %11, %12, %13, %14, %15, %16, %17, %18, %19, %20, %21, %22, %23, %24, %25, %26, %27, %28, %29, %30, %31, %32, %33, %34, %35, %36, %37, %38, %39, %40, %41, %42, %43, %44, %45, %46, %47, %48, %49, %50, %51, %52, %53, %54, %55, %56, %57, %58, %59, %60, %61, %62, %63}, "
    "{%64, %65, %66, %67}, bd, p, 1, 1, 1;\n}\n"
    : "+f"(d[0]), "+f"(d[1]), "+f"(d[2]), "+f"(d[3]), "+f"(d[4]), "+f"(d[5]), "+f"(d[6]), "+f"(d[7]), "+f"(d[8]), "+f"(d[9]), "+f"(d[10]), "+f"(d[11]), "+f"(d[12]), "+f"(d[13]), "+f"(d[14]), "+f"(d[15]), "+f"(d[16]), "+f"(d[17]), "+f"(d[18]), "+f"(d[19]), "+f"(d[20]), "+f"(d[21]), "+f"(d[22]), "+f"(d[23]), "+f"(d[24]), "+f"(d[25]), "+f"(d[26]), "+f"(d[27]), "+f"(d[28]), "+f"(d[29]), "+f"(d[30]), "+f"(d[31]), "+f"(d[32]), "+f"(d[33]), "+f"(d[34]), "+f"(d[35]), "+f"(d[36]), "+f"(d[37]), "+f"(d[38]), "+f"(d[39]), "+f"(d[40]), "+f"(d[41]), "+f"(d[42]), "+f"(d[43]), "+f"(d[44]), "+f"(d[45]), "+f"(d[46]), "+f"(d[47]), "+f"(d[48]), "+f"(d[49]), "+f"(d[50]), "+f"(d[51]), "+f"(d[52]), "+f"(d[53]), "+f"(d[54]), "+f"(d[55]), "+f"(d[56]), "+f"(d[57]), "+f"(d[58]), "+f"(d[59]), "+f"(d[60]), "+f"(d[61]), "+f"(d[62]), "+f"(d[63])
    : "r"(a0), "r"(a1), "r"(a2), "r"(a3), "n"(BD));
}
template<int SD, uint64_t BD, int SZ> __device__ __forceinline__ void wg_rs120(float (&d)[SZ], uint32_t a0, uint32_t a1, uint32_t a2, uint32_t a3) {
  if constexpr (SD == 0)
  asm volatile("{\n.reg .pred p;\n.reg .b64 ad, bd;\n.reg .b32 lo;\nsetp.ne.b32 p, 0, 0;\n"
    "mov.b64 bd, %64;\n"
    "wgmma.mma_async.sync.aligned.m64n120k16.f32.bf16.bf16 "
    "{%0, %1, %2, %3, %4, %5, %6, %7, %8, %9, %10, %11, %12, %13, %14, %15, %16, %17, %18, %19, %20, %21, %22, %23, %24, %25, %26, %27, %28, %29, %30, %31, %32, %33, %34, %35, %36, %37, %38, %39, %40, %41, %42, %43, %44, %45, %46, %47, %48, %49, %50, %51, %52, %53, %54, %55, %56, %57, %58, %59}, "
    "{%60, %61, %62, %63}, bd, p, 1, 1, 1;\n}\n"
    : "=f"(d[0]), "=f"(d[1]), "=f"(d[2]), "=f"(d[3]), "=f"(d[4]), "=f"(d[5]), "=f"(d[6]), "=f"(d[7]), "=f"(d[8]), "=f"(d[9]), "=f"(d[10]), "=f"(d[11]), "=f"(d[12]), "=f"(d[13]), "=f"(d[14]), "=f"(d[15]), "=f"(d[16]), "=f"(d[17]), "=f"(d[18]), "=f"(d[19]), "=f"(d[20]), "=f"(d[21]), "=f"(d[22]), "=f"(d[23]), "=f"(d[24]), "=f"(d[25]), "=f"(d[26]), "=f"(d[27]), "=f"(d[28]), "=f"(d[29]), "=f"(d[30]), "=f"(d[31]), "=f"(d[32]), "=f"(d[33]), "=f"(d[34]), "=f"(d[35]), "=f"(d[36]), "=f"(d[37]), "=f"(d[38]), "=f"(d[39]), "=f"(d[40]), "=f"(d[41]), "=f"(d[42]), "=f"(d[43]), "=f"(d[44]), "=f"(d[45]), "=f"(d[46]), "=f"(d[47]), "=f"(d[48]), "=f"(d[49]), "=f"(d[50]), "=f"(d[51]), "=f"(d[52]), "=f"(d[53]), "=f"(d[54]), "=f"(d[55]), "=f"(d[56]), "=f"(d[57]), "=f"(d[58]), "=f"(d[59])
    : "r"(a0), "r"(a1), "r"(a2), "r"(a3), "n"(BD));
  if constexpr (SD == 1)
  asm volatile("{\n.reg .pred p;\n.reg .b64 ad, bd;\n.reg .b32 lo;\nsetp.ne.b32 p, 1, 0;\n"
    "mov.b64 bd, %64;\n"
    "wgmma.mma_async.sync.aligned.m64n120k16.f32.bf16.bf16 "
    "{%0, %1, %2, %3, %4, %5, %6, %7, %8, %9, %10, %11, %12, %13, %14, %15, %16, %17, %18, %19, %20, %21, %22, %23, %24, %25, %26, %27, %28, %29, %30, %31, %32, %33, %34, %35, %36, %37, %38, %39, %40, %41, %42, %43, %44, %45, %46, %47, %48, %49, %50, %51, %52, %53, %54, %55, %56, %57, %58, %59}, "
    "{%60, %61, %62, %63}, bd, p, 1, 1, 1;\n}\n"
    : "+f"(d[0]), "+f"(d[1]), "+f"(d[2]), "+f"(d[3]), "+f"(d[4]), "+f"(d[5]), "+f"(d[6]), "+f"(d[7]), "+f"(d[8]), "+f"(d[9]), "+f"(d[10]), "+f"(d[11]), "+f"(d[12]), "+f"(d[13]), "+f"(d[14]), "+f"(d[15]), "+f"(d[16]), "+f"(d[17]), "+f"(d[18]), "+f"(d[19]), "+f"(d[20]), "+f"(d[21]), "+f"(d[22]), "+f"(d[23]), "+f"(d[24]), "+f"(d[25]), "+f"(d[26]), "+f"(d[27]), "+f"(d[28]), "+f"(d[29]), "+f"(d[30]), "+f"(d[31]), "+f"(d[32]), "+f"(d[33]), "+f"(d[34]), "+f"(d[35]), "+f"(d[36]), "+f"(d[37]), "+f"(d[38]), "+f"(d[39]), "+f"(d[40]), "+f"(d[41]), "+f"(d[42]), "+f"(d[43]), "+f"(d[44]), "+f"(d[45]), "+f"(d[46]), "+f"(d[47]), "+f"(d[48]), "+f"(d[49]), "+f"(d[50]), "+f"(d[51]), "+f"(d[52]), "+f"(d[53]), "+f"(d[54]), "+f"(d[55]), "+f"(d[56]), "+f"(d[57]), "+f"(d[58]), "+f"(d[59])
    : "r"(a0), "r"(a1), "r"(a2), "r"(a3), "n"(BD));
}
template<int SD, uint64_t BD, int SZ> __device__ __forceinline__ void wg_rs64(float (&d)[SZ], uint32_t a0, uint32_t a1, uint32_t a2, uint32_t a3) {
  if constexpr (SD == 0)
  asm volatile("{\n.reg .pred p;\n.reg .b64 ad, bd;\n.reg .b32 lo;\nsetp.ne.b32 p, 0, 0;\n"
    "mov.b64 bd, %36;\n"
    "wgmma.mma_async.sync.aligned.m64n64k16.f32.bf16.bf16 "
    "{%0, %1, %2, %3, %4, %5, %6, %7, %8, %9, %10, %11, %12, %13, %14, %15, %16, %17, %18, %19, %20, %21, %22, %23, %24, %25, %26, %27, %28, %29, %30, %31}, "
    "{%32, %33, %34, %35}, bd, p, 1, 1, 1;\n}\n"
    : "=f"(d[0]), "=f"(d[1]), "=f"(d[2]), "=f"(d[3]), "=f"(d[4]), "=f"(d[5]), "=f"(d[6]), "=f"(d[7]), "=f"(d[8]), "=f"(d[9]), "=f"(d[10]), "=f"(d[11]), "=f"(d[12]), "=f"(d[13]), "=f"(d[14]), "=f"(d[15]), "=f"(d[16]), "=f"(d[17]), "=f"(d[18]), "=f"(d[19]), "=f"(d[20]), "=f"(d[21]), "=f"(d[22]), "=f"(d[23]), "=f"(d[24]), "=f"(d[25]), "=f"(d[26]), "=f"(d[27]), "=f"(d[28]), "=f"(d[29]), "=f"(d[30]), "=f"(d[31])
    : "r"(a0), "r"(a1), "r"(a2), "r"(a3), "n"(BD));
  if constexpr (SD == 1)
  asm volatile("{\n.reg .pred p;\n.reg .b64 ad, bd;\n.reg .b32 lo;\nsetp.ne.b32 p, 1, 0;\n"
    "mov.b64 bd, %36;\n"
    "wgmma.mma_async.sync.aligned.m64n64k16.f32.bf16.bf16 "
    "{%0, %1, %2, %3, %4, %5, %6, %7, %8, %9, %10, %11, %12, %13, %14, %15, %16, %17, %18, %19, %20, %21, %22, %23, %24, %25, %26, %27, %28, %29, %30, %31}, "
    "{%32, %33, %34, %35}, bd, p, 1, 1, 1;\n}\n"
    : "+f"(d[0]), "+f"(d[1]), "+f"(d[2]), "+f"(d[3]), "+f"(d[4]), "+f"(d[5]), "+f"(d[6]), "+f"(d[7]), "+f"(d[8]), "+f"(d[9]), "+f"(d[10]), "+f"(d[11]), "+f"(d[12]), "+f"(d[13]), "+f"(d[14]), "+f"(d[15]), "+f"(d[16]), "+f"(d[17]), "+f"(d[18]), "+f"(d[19]), "+f"(d[20]), "+f"(d[21]), "+f"(d[22]), "+f"(d[23]), "+f"(d[24]), "+f"(d[25]), "+f"(d[26]), "+f"(d[27]), "+f"(d[28]), "+f"(d[29]), "+f"(d[30]), "+f"(d[31])
    : "r"(a0), "r"(a1), "r"(a2), "r"(a3), "n"(BD));
}
__device__ __forceinline__ void poll4(uint32_t (&v)[32], const void* p, uint32_t tag) {
  asm volatile("{\n.reg .pred p;\n.reg .b32 t0, t1, c;\nmov.u32 c, 0;\nPL_LOOP:\n"
    "lop3.b32 t0, %0, %2, %33, 0x7E;\n"
    "lop3.b32 t1, %4, %6, %33, 0x7E;\nor.b32 t0, t0, t1;\n"
    "lop3.b32 t1, %8, %10, %33, 0x7E;\nor.b32 t0, t0, t1;\n"
    "lop3.b32 t1, %12, %14, %33, 0x7E;\nor.b32 t0, t0, t1;\n"
    "lop3.b32 t1, %16, %18, %33, 0x7E;\nor.b32 t0, t0, t1;\n"
    "lop3.b32 t1, %20, %22, %33, 0x7E;\nor.b32 t0, t0, t1;\n"
    "lop3.b32 t1, %24, %26, %33, 0x7E;\nor.b32 t0, t0, t1;\n"
    "lop3.b32 t1, %28, %30, %33, 0x7E;\nor.b32 t0, t0, t1;\n"
    "and.b32 t0, t0, 1;\nsetp.eq.u32 p, t0, 0;\n@p bra PL_DONE;\n"
    "ld.relaxed.gpu.global.v4.b32 {%0, %1, %2, %3}, [%32+0];\n"
    "ld.relaxed.gpu.global.v4.b32 {%4, %5, %6, %7}, [%32+4096];\n"
    "ld.relaxed.gpu.global.v4.b32 {%8, %9, %10, %11}, [%32+8192];\n"
    "ld.relaxed.gpu.global.v4.b32 {%12, %13, %14, %15}, [%32+12288];\n"
    "ld.relaxed.gpu.global.v4.b32 {%16, %17, %18, %19}, [%32+16384];\n"
    "ld.relaxed.gpu.global.v4.b32 {%20, %21, %22, %23}, [%32+20480];\n"
    "ld.relaxed.gpu.global.v4.b32 {%24, %25, %26, %27}, [%32+24576];\n"
    "ld.relaxed.gpu.global.v4.b32 {%28, %29, %30, %31}, [%32+28672];\n"
    "add.u32 c, c, 1;\nsetp.lt.u32 p, c, 2000000;\n@p bra PL_LOOP;\ntrap;\nPL_DONE:\n}\n"
    : "+r"(v[0]), "+r"(v[1]), "+r"(v[2]), "+r"(v[3]), "+r"(v[4]), "+r"(v[5]), "+r"(v[6]), "+r"(v[7]), "+r"(v[8]), "+r"(v[9]), "+r"(v[10]), "+r"(v[11]), "+r"(v[12]), "+r"(v[13]), "+r"(v[14]), "+r"(v[15]), "+r"(v[16]), "+r"(v[17]), "+r"(v[18]), "+r"(v[19]), "+r"(v[20]), "+r"(v[21]), "+r"(v[22]), "+r"(v[23]), "+r"(v[24]), "+r"(v[25]), "+r"(v[26]), "+r"(v[27]), "+r"(v[28]), "+r"(v[29]), "+r"(v[30]), "+r"(v[31])
    : "l"(p), "r"(tag) : "memory");
}
__device__ __forceinline__ void poll2(uint32_t (&v)[16], const void* p, uint32_t tag) {
  asm volatile("{\n.reg .pred p;\n.reg .b32 t0, t1, c;\nmov.u32 c, 0;\nPL_LOOP:\n"
    "lop3.b32 t0, %0, %2, %17, 0x7E;\n"
    "lop3.b32 t1, %4, %6, %17, 0x7E;\nor.b32 t0, t0, t1;\n"
    "lop3.b32 t1, %8, %10, %17, 0x7E;\nor.b32 t0, t0, t1;\n"
    "lop3.b32 t1, %12, %14, %17, 0x7E;\nor.b32 t0, t0, t1;\n"
    "and.b32 t0, t0, 1;\nsetp.eq.u32 p, t0, 0;\n@p bra PL_DONE;\n"
    "ld.relaxed.gpu.global.v2.b32 {%0, %1}, [%16+0];\n"
    "ld.relaxed.gpu.global.v2.b32 {%2, %3}, [%16+2048];\n"
    "ld.relaxed.gpu.global.v2.b32 {%4, %5}, [%16+4096];\n"
    "ld.relaxed.gpu.global.v2.b32 {%6, %7}, [%16+6144];\n"
    "ld.relaxed.gpu.global.v2.b32 {%8, %9}, [%16+8192];\n"
    "ld.relaxed.gpu.global.v2.b32 {%10, %11}, [%16+10240];\n"
    "ld.relaxed.gpu.global.v2.b32 {%12, %13}, [%16+12288];\n"
    "ld.relaxed.gpu.global.v2.b32 {%14, %15}, [%16+14336];\n"
    "add.u32 c, c, 1;\nsetp.lt.u32 p, c, 2000000;\n@p bra PL_LOOP;\ntrap;\nPL_DONE:\n}\n"
    : "+r"(v[0]), "+r"(v[1]), "+r"(v[2]), "+r"(v[3]), "+r"(v[4]), "+r"(v[5]), "+r"(v[6]), "+r"(v[7]), "+r"(v[8]), "+r"(v[9]), "+r"(v[10]), "+r"(v[11]), "+r"(v[12]), "+r"(v[13]), "+r"(v[14]), "+r"(v[15])
    : "l"(p), "r"(tag) : "memory");
}

constexpr uint64_t dB128 = make_desc(SB, 8192, 1024, 1);
constexpr uint64_t dB128h = make_desc(SB, 4096, 1024, 1);
constexpr uint64_t dB64 = make_desc(SB, 4096, 512, 2);
constexpr uint64_t dA = make_desc(SB + OFF_X, 16, 1024, 1);
template<int I> struct IC { static constexpr int value = I; };
template<int B, int E, class F> __device__ __forceinline__ void sfor(F&& f) { if constexpr (B < E) { f(IC<B>{}); sfor<B + 1, E>(f); } }
#define SFOR(VAR, B, E) sfor<B, E>([&](auto VAR##_) __attribute__((always_inline)) { constexpr int VAR = decltype(VAR##_)::value;
#define SEND });

struct RowC { float c0, c1, c2; };

template<int LO, int HI, int NP, int HOFF>
__device__ __forceinline__ void geglu_slice(uint32_t (&hp)[56], float (&acc)[64], const RowC& a, const RowC& b) {
  #pragma unroll
  for (int i = LO; i < HI; i++) {
    const RowC& c = (i & 1) ? b : a;
    hp[HOFF + i] = pack2(geglu1(acc[2 * i], acc[2 * NP + 2 * i], c.c0, c.c1, c.c2), geglu1(acc[2 * i + 1], acc[2 * NP + 2 * i + 1], c.c0, c.c1, c.c2));
  }
}
template<int NJP>
__device__ __forceinline__ void send_part(float (&acc)[64], uint4* dst, uint32_t tag) {
  #pragma unroll
  for (int jp = 0; jp < NJP; jp++) {
    uint32_t r0 = pack2(acc[8 * jp], acc[8 * jp + 1]), r1 = pack2(acc[8 * jp + 2], acc[8 * jp + 3]);
    uint32_t r2 = pack2(acc[8 * jp + 4], acc[8 * jp + 5]), r3 = pack2(acc[8 * jp + 6], acc[8 * jp + 7]);
    r0 = (r0 & ~1u) | tag; r2 = (r2 & ~1u) | tag;
    asm volatile("st.relaxed.gpu.global.v4.b32 [%0], {%1, %2, %3, %4};" :: "l"(dst + jp * 32), "r"(r0), "r"(r1), "r"(r2), "r"(r3) : "memory");
  }
}
__device__ __forceinline__ void gather4_issue(uint32_t (&v)[32], const uint4* p) {
  #pragma unroll
  for (int i = 0; i < 8; i++)
    asm volatile("ld.relaxed.gpu.global.v4.b32 {%0, %1, %2, %3}, [%4];" : "=r"(v[4 * i]), "=r"(v[4 * i + 1]), "=r"(v[4 * i + 2]), "=r"(v[4 * i + 3]) : "l"(p + i * 256) : "memory");
}
__device__ __forceinline__ float untag_lo(uint32_t u) { return __uint_as_float(((u << 16) & 0xFFFE0000u) | 0x8000u); }
__device__ __forceinline__ void resid4(uint32_t (&xr)[4], const __nv_bfloat16* x, int xo) {
  xr[0] = __ldg((const unsigned*)(x + xo)); xr[1] = __ldg((const unsigned*)(x + xo + 8 * DM));
  xr[2] = __ldg((const unsigned*)(x + xo + 8)); xr[3] = __ldg((const unsigned*)(x + xo + 8 * DM + 8));
}
__device__ __forceinline__ void gather4_finish(uint32_t (&v)[32], uint32_t (&xr)[4], __nv_bfloat16* out, int xo) {
  float a[8];
  #pragma unroll
  for (int k = 0; k < 4; k++) { a[2 * k] = bf_lo(xr[k]); a[2 * k + 1] = bf_hi(xr[k]); }
  #pragma unroll
  for (int i = 0; i < 8; i++) {
    #pragma unroll
    for (int k = 0; k < 4; k++) { uint32_t u = v[4 * i + k]; a[2 * k] += (k & 1) ? bf_lo(u) : untag_lo(u); a[2 * k + 1] += bf_hi(u); }
  }
  *(unsigned*)(out + xo) = pack2(a[0], a[1]); *(unsigned*)(out + xo + 8 * DM) = pack2(a[2], a[3]);
  *(unsigned*)(out + xo + 8) = pack2(a[4], a[5]); *(unsigned*)(out + xo + 8 * DM + 8) = pack2(a[6], a[7]);
}

__global__ void __launch_bounds__(384, 1)
fused_kernel(const __grid_constant__ Maps maps, const __nv_bfloat16* __restrict__ x, __nv_bfloat16* __restrict__ out) {
  extern __shared__ __align__(1024) char smraw[];
  constexpr uint32_t sb = SB;
  const int tid = threadIdx.x;
  const int mt = blockIdx.x >> 3, s = blockIdx.x & 7;
  const int wg = __shfl_sync(0xffffffffu, tid >> 7, 0);
  STAMP(0);
  if (tid == 256) {
    if (smem_u32(smraw) != SB) __trap();
    #pragma unroll
    for (int i = 0; i < 7; i++) { mbar_init(sb + BAR_X + 8 * i, 1); mbar_init(sb + BAR_FULL + 8 * i, 1); }
    asm volatile("fence.mbarrier_init.release.cluster;" ::: "memory");
    fence_async();
    #pragma unroll
    for (int i = 0; i < 7; i++) { mbar_expect_tx(sb + BAR_X + 8 * i, 16384); tma2d(sb + OFF_X + i * 16384, &maps.x, sb + BAR_X + 8 * i, i * 64, mt * 128); }
    #pragma unroll
    for (int t = 0; t < 7; t++) {
      mbar_expect_tx(sb + BAR_FULL + 8 * t, 16384);
      tma2d(sb + buf_off(t), &maps.qkv, sb + BAR_FULL + 8 * t, 448 + 56 * s, t * 64);
      tma2d(sb + buf_off(t) + 8192, &maps.qkv, sb + BAR_FULL + 8 * t, 896 + 56 * s, t * 64);
    }
  } else if (tid < 46) {
    mbar_init(sb + BAR_FULL + 8 * (tid + 7), 1);
  } else if (tid >= 64 && tid < 104) {
    mbar_init(sb + BAR_EMPTY + 8 * (tid - 64), 2);
  } else if (tid == 128) {
    mbar_init(sb + BAR_KVP, 128); mbar_init(sb + BAR_KVP + 8, 128); mbar_init(sb + BAR_KVREAD, 1); mbar_init(sb + BAR_KVB, 1);
  }
  if (tid < 256) { asm volatile("fence.mbarrier_init.release.cluster;" ::: "memory"); fence_async(); }
  __syncthreads();

  if (wg == 2) {
    asm volatile("setmaxnreg.dec.sync.aligned.u32 40;");
    const int warp = (tid >> 5) & 3, lane = tid & 31;
    if (warp == 0) {
      if (lane == 0) {
        #pragma unroll
        for (int t = 7; t < 53; t++) {
          const int dp = dep_of(t);
          mbar_wait(dp == -2 ? sb + BAR_KVREAD : sb + BAR_EMPTY + 8 * dp);
          const uint32_t fb = sb + BAR_FULL + 8 * t, dst = sb + buf_off(t);
          if (t < 14) {
            const int kb = t - 7;
            mbar_expect_tx(fb, 16384);
            tma2d(dst, &maps.g64, fb, 224 * s + 192, kb * 64);
            tma2d(dst + 4096, &maps.u64, fb, 224 * s + 192, kb * 64);
            tma2d(dst + 8192, &maps.q64, fb, 56 * s, kb * 64);
            tma2d(dst + 12288, &maps.q64, fb, 56 * s + 32, kb * 64);
          } else if (t < 35) {
            const int kb = (t - 14) % 7, ci = (t - 14) / 7;
            mbar_expect_tx(fb, 16384);
            tma2d(dst, &maps.g, fb, 224 * s + 64 * ci, kb * 64);
            tma2d(dst + 8192, &maps.u, fb, 224 * s + 64 * ci, kb * 64);
          } else if (t < 50) {
            const int p = (t - 35) / 5, st = (t - 35) % 5;
            if (st == 0) {
              mbar_expect_tx(fb, 16384);
              tma2d(dst, &maps.o, fb, 128 * p, 56 * s);
              tma2d(dst + 8192, &maps.o, fb, 128 * p + 64, 56 * s);
            } else if (st == 1) {
              mbar_expect_tx(fb, 8192);
              tma2d(dst, &maps.d32, fb, 128 * p, 224 * s + 192);
              tma2d(dst + 4096, &maps.d32, fb, 128 * p + 64, 224 * s + 192);
            } else {
              mbar_expect_tx(fb, 16384);
              tma2d(dst, &maps.d, fb, 128 * p, 224 * s + 64 * (st - 2));
              tma2d(dst + 8192, &maps.d, fb, 128 * p + 64, 224 * s + 64 * (st - 2));
            }
          } else if (t == 50) {
            mbar_expect_tx(fb, 12288);
            tma2d(dst, &maps.o, fb, 384, 56 * s);
            tma2d(dst + 8192, &maps.d32, fb, 384, 224 * s + 192);
          } else if (t == 51) {
            mbar_expect_tx(fb, 16384);
            tma2d(dst, &maps.d, fb, 384, 224 * s);
            tma2d(dst + 8192, &maps.d, fb, 384, 224 * s + 64);
          } else {
            mbar_expect_tx(fb, 8192);
            tma2d(dst, &maps.d, fb, 384, 224 * s + 128);
          }
        }
        STAMPW(1);
      }
    } else if (warp == 1) {
      unsigned* cnt = &g_cnt[s * 32];
      unsigned e = 0;
      if (lane == 0) { asm volatile("ld.relaxed.gpu.global.u32 %0, [%1];" : "=r"(e) : "l"(cnt) : "memory"); e >>= 4; }
      e = __shfl_sync(0xffffffffu, e, 0);
      const unsigned par = e & 1;
      if (lane == 0) asm volatile("st.shared.u32 [%0], %1;" :: "r"(sb + OFF_TAG), "r"(par ^ 1u) : "memory");
      if (mt == 0) {
        float4* z = (float4*)&g_kvsum[((par ^ 1u) * 8 + s) * 1792];
        #pragma unroll
        for (int i = 0; i < 14; i++) z[lane + 32 * i] = make_float4(0.f, 0.f, 0.f, 0.f);
      }
      float* sum = &g_kvsum[(par * 8 + s) * 1792];
      mbar_wait(sb + BAR_KVP);
      if (lane == 0) {
        asm volatile("cp.reduce.async.bulk.global.shared::cta.bulk_group.add.f32 [%0], [%1], %2;" :: "l"(sum), "r"(sb + OFF_SLOT + 5 * 16384), "r"(7168) : "memory");
        asm volatile("cp.async.bulk.commit_group;" ::: "memory");
      }
      mbar_wait(sb + BAR_KVP + 8);
      STAMPW(2);
      if (lane == 0) {
        asm volatile("cp.reduce.async.bulk.global.shared::cta.bulk_group.add.f32 [%0], [%1], %2;" :: "l"(sum), "r"(sb + OFF_SLOT + 6 * 16384), "r"(7168) : "memory");
        asm volatile("cp.async.bulk.commit_group;" ::: "memory");
        asm volatile("cp.async.bulk.wait_group.read 1;" ::: "memory");
        mbar_arrive(sb + BAR_KVREAD);
      }
      #pragma unroll
      for (int i = 0; i < 16; i++)
        asm volatile("st.shared.v4.u32 [%0], {%1, %1, %1, %1};" :: "r"(sb + OFF_KVB + (lane + 32 * i) * 16), "r"(0) : "memory");
      if (lane == 0) {
        asm volatile("cp.async.bulk.wait_group 0;" ::: "memory");
        asm volatile("fence.proxy.async;" ::: "memory");
        __threadfence();
        asm volatile("red.release.gpu.global.add.u32 [%0], 1;" :: "l"(cnt) : "memory");
        STAMPW(3);
        const unsigned base = e << 4;
        asm volatile("{\n.reg .pred p;\n.reg .u32 c, v;\nmov.u32 c, 0;\nKV_LOOP:\n"
          "ld.acquire.gpu.global.u32 v, [%0];\nsub.u32 v, v, %1;\nsetp.ge.u32 p, v, 16;\n@p bra KV_DONE;\n"
          "nanosleep.u32 64;\nadd.u32 c, c, 1;\nsetp.lt.u32 p, c, 2000000;\n@p bra KV_LOOP;\ntrap;\nKV_DONE:\n}\n" :: "l"(cnt), "r"(base) : "memory");
        asm volatile("fence.proxy.async;" ::: "memory");
      }
      __syncwarp();
      STAMPW(4);
      #pragma unroll
      for (int bt = 0; bt < 2; bt++) {
        float4 v[7];
        #pragma unroll
        for (int n = 0; n < 7; n++) {
          const float* p = sum + (lane + 32 * (bt * 7 + n)) * 4;
          asm volatile("ld.relaxed.gpu.global.v4.f32 {%0, %1, %2, %3}, [%4];" : "=f"(v[n].x), "=f"(v[n].y), "=f"(v[n].z), "=f"(v[n].w) : "l"(p) : "memory");
        }
        #pragma unroll
        for (int n = 0; n < 7; n++) {
          const int i = lane + 32 * (bt * 7 + n);
          const int d = i >> 3, f = (i & 7) ^ ((d & 3) << 1);
          const bool hB = d >= 28;
          uint32_t w0 = pack2(v[n].x, v[n].y), w1 = pack2(v[n].z, v[n].w);
          int hc = f + (hB ? 7 : 0);
          if (f == 7) { hc = 14; w0 = hB ? (w0 << 16) : (w0 & 0xFFFFu); w1 = 0; }
          asm volatile("st.shared.v2.u32 [%0], {%1, %2};" :: "r"(sb + OFF_KVB + d * 128 + (((hc >> 1) ^ (d & 7)) << 4) + (hc & 1) * 8), "r"(w0), "r"(w1) : "memory");
        }
      }
      fence_async();
      __syncwarp();
      if (lane == 0) mbar_arrive(sb + BAR_KVB);
      STAMPW(5);
    }
    return;
  }

  asm volatile("setmaxnreg.inc.sync.aligned.u32 232;");
  const int lane = tid & 31, wl = (tid >> 5) & 3, w8 = tid >> 5;
  const int q = lane & 3;
  const uint32_t is0 = (tid & 127) == 0;
  constexpr uint32_t fb = sb + BAR_FULL, eb = sb + BAR_EMPTY;
  const uint32_t aoff = wg * 512;
  const uint32_t lrow = (lane & 7) + ((lane >> 3) & 1) * 8, lhi = lane >> 4, l7 = lane & 7;

  float accA[64], accB[64];
  uint32_t hp[56];
  RowC ca, cb;
  float ra, rb;
  {
    uint32_t xr[112];
    float s0[4] = {0.f, 0.f, 0.f, 0.f}, s1[4] = {0.f, 0.f, 0.f, 0.f};
    const uint32_t xrow = sb + OFF_X + (w8 * 16 + lrow) * 128;
    #pragma unroll
    for (int kb = 0; kb < 7; kb++) {
      mbar_wait(sb + BAR_X + 8 * kb);
      #pragma unroll
      for (int kk = 0; kk < 4; kk++) {
        const int i = (kb * 4 + kk) * 4;
        ldsm4(xr[i], xr[i + 1], xr[i + 2], xr[i + 3], xrow + kb * 16384 + (((2 * kk + lhi) ^ l7) << 4));
      }
      #pragma unroll
      for (int kk = 0; kk < 4; kk++) {
        const int i = (kb * 4 + kk) * 4;
        if (kk & 1) mma_rowsum(s1, xr[i], xr[i + 1], xr[i + 2], xr[i + 3]); else mma_rowsum(s0, xr[i], xr[i + 1], xr[i + 2], xr[i + 3]);
      }
    }
    STAMP(1);
    const float meanA = (s0[0] + s1[0]) * (1.0f / DM), meanB = (s0[2] + s1[2]) * (1.0f / DM);
    const uint32_t mA = pack2(meanA, meanA), mB = pack2(meanB, meanB);
    float vA = 0.f, vB = 0.f;
    #pragma unroll
    for (int i = 0; i < 16; i++) xr[i] = hsub2(xr[i], (i & 1) ? mB : mA);
    SFOR(kb, 0, 7)
      mbar_wait(fb + 8 * kb);
      wg_fence();
      SFOR(kk, 0, 4)
        constexpr int i = (kb * 4 + kk) * 4;
        wg_rs120<(kb | kk) != 0, dB128 + ((buf_off(kb) + kk * 2048) >> 4)>(accA, xr[i], xr[i + 1], xr[i + 2], xr[i + 3]);
      SEND
      wg_commit();
      if constexpr (kb < 6) {
        #pragma unroll
        for (int i = 16 * (kb + 1); i < 16 * (kb + 2); i++) xr[i] = hsub2(xr[i], (i & 1) ? mB : mA);
      }
      if constexpr (kb > 0) { wg_wait<1>(); mbar_arrive_pred(eb + 8 * (kb - 1), is0); }
      #pragma unroll
      for (int kk = 0; kk < 4; kk++) {
        const int i = (kb * 4 + kk) * 4;
        stsm4(xrow + kb * 16384 + (((2 * kk + lhi) ^ l7) << 4), xr[i], xr[i + 1], xr[i + 2], xr[i + 3]);
      }
      #pragma unroll
      for (int i = 16 * kb; i < 16 * (kb + 1); i++) {
        const float lo = bf_lo(xr[i]), hi = bf_hi(xr[i]);
        if (i & 1) { vB = fmaf(lo, lo, vB); vB = fmaf(hi, hi, vB); } else { vA = fmaf(lo, lo, vA); vA = fmaf(hi, hi, vA); }
      }
    SEND
    fence_async();
    wg_bar(wg);
    vA += __shfl_xor_sync(0xffffffffu, vA, 1); vB += __shfl_xor_sync(0xffffffffu, vB, 1);
    vA += __shfl_xor_sync(0xffffffffu, vA, 2); vB += __shfl_xor_sync(0xffffffffu, vB, 2);
    const float dA_ = meanA - bf_lo(mA), dB_ = meanB - bf_lo(mB);
    vA = fmaxf(fmaf(vA, 1.0f / DM, -dA_ * dA_), 0.f); vB = fmaxf(fmaf(vB, 1.0f / DM, -dB_ * dB_), 0.f);
    ra = 1.0f / bf_round(sqrtf(bf_round(bf_round(vA) + 1e-5f)));
    rb = 1.0f / bf_round(sqrtf(bf_round(bf_round(vB) + 1e-5f)));
    ca.c0 = 0.7978845608f * ra; ca.c1 = 0.0356774081f * ra * ra * ra; ca.c2 = 0.5f * ra * ra;
    cb.c0 = 0.7978845608f * rb; cb.c1 = 0.0356774081f * rb * rb * rb; cb.c2 = 0.5f * rb * rb;
  }
  STAMP(2);
  const float rla = ra * 1.4426950409f, rlb = rb * 1.4426950409f;
  {
    float (&kvacc)[64] = accA;
    uint32_t pk[14];
    const uint32_t tile = sb + OFF_SLOT + (5 + wg) * 16384;
    const uint32_t trow = tile + (wl * 16 + lrow) * 128;
    constexpr uint64_t dKV = dB128 + ((OFF_SLOT + 5 * 16384) >> 4);
    SFOR(kb, 0, 7)
      constexpr int t = 7 + kb;
      mbar_wait(fb + 8 * t);
      wg_fence();
      SFOR(kk, 0, 4)
        wg_ss120<(kb | kk) != 0, dA + ((kb * 16384 + kk * 32) >> 4), dB64 + ((buf_off(t) + kk * 1024) >> 4)>(accB, aoff);
      SEND
      if constexpr (kb == 4) {
        wg_ss64t<0, dKV, dKV + 512>(kvacc, 2 * aoff);
        wg_ss64t<1, dKV + 128, dKV + 512 + 128>(kvacc, 2 * aoff);
        wg_ss64t<1, dKV + 256, dKV + 512 + 256>(kvacc, 2 * aoff);
        wg_ss64t<1, dKV + 384, dKV + 512 + 384>(kvacc, 2 * aoff);
      }
      wg_commit();
      wg_wait<1>();
      if constexpr (kb == 0) fence_regs<0, 60>(accA);
      mbar_arrive_pred(eb + 8 * (t - 1), is0);
      if constexpr (kb == 0) {
        #pragma unroll
        for (int i = 0; i < 8; i++) pk[i] = (i & 1) ? phi2(accA[2 * i], accA[2 * i + 1], rb, rlb) : phi2(accA[2 * i], accA[2 * i + 1], ra, rla);
      } else if constexpr (kb == 1) {
        #pragma unroll
        for (int i = 8; i < 14; i++) pk[i] = (i & 1) ? phi2(accA[2 * i], accA[2 * i + 1], rb, rlb) : phi2(accA[2 * i], accA[2 * i + 1], ra, rla);
        mbar_wait(eb + 8 * (5 + wg));
        #pragma unroll
        for (int jj = 0; jj < 3; jj++) stsm4(trow + (((2 * jj + lhi) ^ l7) << 4), pk[4 * jj], pk[4 * jj + 1], pk[4 * jj + 2], pk[4 * jj + 3]);
        stsm4(trow + (((6 + lhi) ^ l7) << 4), pk[12], pk[13], 0u, 0u);
      } else if constexpr (kb == 2) {
        uint32_t vv[14];
        #pragma unroll
        for (int i = 0; i < 14; i++) { const float r = (i & 1) ? rb : ra; vv[i] = pack2(accA[32 + 2 * i] * r, accA[33 + 2 * i] * r); }
        #pragma unroll
        for (int jj = 0; jj < 3; jj++) stsm4(trow + 8192 + (((2 * jj + lhi) ^ l7) << 4), vv[4 * jj], vv[4 * jj + 1], vv[4 * jj + 2], vv[4 * jj + 3]);
        const uint32_t one = q == 0 ? 0x00003F80u : 0u;
        stsm4(trow + 8192 + (((6 + lhi) ^ l7) << 4), vv[12], vv[13], one, one);
        fence_async();
      } else if constexpr (kb == 3) {
        wg_bar(wg);
      } else if constexpr (kb == 5) {
        fence_regs<0, 32>(kvacc);
        wg_bar(wg);
        #pragma unroll
        for (int hf = 0; hf < 2; hf++) {
          const int d = wl * 16 + (lane >> 2) + hf * 8;
          const bool hB = d >= 28;
          const uint32_t rowa = tile + d * 128;
          const int sw = (d & 3) << 3;
          #pragma unroll
          for (int j = 0; j < 8; j++) {
            const int col = 8 * j + 2 * q;
            bool ok; int c;
            if (j < 7) { ok = hB ? (col >= 28) : (col < 28); c = hB ? col - 28 : col; } else { ok = q < 2; c = 28 + 2 * q; }
            ok = ok && d < 56;
            asm volatile("{\n.reg .pred p;\nsetp.ne.u32 p, %3, 0;\n@p st.shared.v2.f32 [%0], {%1, %2};\n}"
              :: "r"(rowa + ((c ^ sw) << 2)), "f"(kvacc[4 * j + 2 * hf]), "f"(kvacc[4 * j + 2 * hf + 1]), "r"((uint32_t)ok) : "memory");
          }
        }
        fence_async();
        mbar_arrive(sb + BAR_KVP + 8 * wg);
      }
    SEND
  }
  STAMP(3);
  uint32_t pq[14];
  SFOR(kb, 0, 7)
    constexpr int t = 14 + kb;
    mbar_wait(fb + 8 * t);
    wg_fence();
    SFOR(kk, 0, 4)
      wg_ss128<(kb | kk) != 0, dA + ((kb * 16384 + kk * 32) >> 4), dB128 + ((buf_off(t) + kk * 2048) >> 4)>(accA, aoff);
    SEND
    wg_commit();
    wg_wait<1>();
    if constexpr (kb == 0) fence_regs<0, 60>(accB);
    mbar_arrive_pred(eb + 8 * (t - 1), is0);
    if constexpr (kb == 0) geglu_slice<0, 3, 8, 0>(hp, accB, ca, cb);
    else if constexpr (kb == 1) geglu_slice<3, 6, 8, 0>(hp, accB, ca, cb);
    else if constexpr (kb == 2) geglu_slice<6, 8, 8, 0>(hp, accB, ca, cb);
    else {
      #pragma unroll
      for (int i = 0; i < 14; i++) if (i >= (kb - 3) * 4 && i < (kb - 2) * 4)
        pq[i] = (i & 1) ? phi2(accB[32 + 2 * i], accB[33 + 2 * i], rb, rlb) : phi2(accB[32 + 2 * i], accB[33 + 2 * i], ra, rla);
    }
  SEND
  STAMP(4);
  SFOR(kb, 0, 7)
    constexpr int t = 21 + kb;
    mbar_wait(fb + 8 * t);
    wg_fence();
    SFOR(kk, 0, 4)
      wg_ss128<(kb | kk) != 0, dA + ((kb * 16384 + kk * 32) >> 4), dB128 + ((buf_off(t) + kk * 2048) >> 4)>(accB, aoff);
    SEND
    wg_commit();
    wg_wait<1>();
    if constexpr (kb == 0) fence_regs<0, 64>(accA);
    mbar_arrive_pred(eb + 8 * (t - 1), is0);
    if constexpr (kb == 0) geglu_slice<0, 3, 16, 8>(hp, accA, ca, cb);
    else if constexpr (kb == 1) geglu_slice<3, 5, 16, 8>(hp, accA, ca, cb);
    else if constexpr (kb == 2) geglu_slice<5, 7, 16, 8>(hp, accA, ca, cb);
    else if constexpr (kb == 3) geglu_slice<7, 10, 16, 8>(hp, accA, ca, cb);
    else if constexpr (kb == 4) geglu_slice<10, 12, 16, 8>(hp, accA, ca, cb);
    else if constexpr (kb == 5) geglu_slice<12, 14, 16, 8>(hp, accA, ca, cb);
    else geglu_slice<14, 16, 16, 8>(hp, accA, ca, cb);
  SEND
  STAMP(5);
  uint32_t op[14];
  uint32_t tag;
  {
    float (&oacc)[64] = accB;
    constexpr uint64_t dKVB = dB128 + (OFF_KVB >> 4);
    SFOR(kb, 0, 7)
      constexpr int t = 28 + kb;
      mbar_wait(fb + 8 * t);
      if constexpr (kb == 5) mbar_wait(sb + BAR_KVB);
      wg_fence();
      SFOR(kk, 0, 4)
        wg_ss128<(kb | kk) != 0, dA + ((kb * 16384 + kk * 32) >> 4), dB128 + ((buf_off(t) + kk * 2048) >> 4)>(accA, aoff);
      SEND
      if constexpr (kb == 5) {
        wg_rs64<0, (dKVB)>(oacc, pq[0], pq[1], pq[2], pq[3]);
        wg_rs64<1, (dKVB + 128)>(oacc, pq[4], pq[5], pq[6], pq[7]);
        wg_rs64<1, (dKVB + 256)>(oacc, pq[8], pq[9], pq[10], pq[11]);
        wg_rs64<1, (dKVB + 384)>(oacc, pq[12], pq[13], 0u, 0u);
      }
      wg_commit();
      wg_wait<1>();
      if constexpr (kb == 0) fence_regs<0, 64>(accB);
      mbar_arrive_pred(eb + 8 * (t - 1), is0);
      if constexpr (kb == 0) geglu_slice<0, 4, 16, 24>(hp, accB, ca, cb);
      else if constexpr (kb == 1) geglu_slice<4, 7, 16, 24>(hp, accB, ca, cb);
      else if constexpr (kb == 2) geglu_slice<7, 10, 16, 24>(hp, accB, ca, cb);
      else if constexpr (kb == 3) geglu_slice<10, 13, 16, 24>(hp, accB, ca, cb);
      else if constexpr (kb == 4) geglu_slice<13, 16, 16, 24>(hp, accB, ca, cb);
      else if constexpr (kb == 6) {
        fence_regs<0, 32>(oacc);
        asm volatile("ld.shared.u32 %0, [%1];" : "=r"(tag) : "r"(sb + OFF_TAG) : "memory");
        float dn[4];
        #pragma unroll
        for (int i = 0; i < 4; i++) dn[i] = rcp(__shfl_sync(0xffffffffu, oacc[28 + i], lane & ~3) + 1e-6f);
        #pragma unroll
        for (int i = 0; i < 14; i++) {
          const int j = i >> 1, hf = i & 1;
          const float dv = j < 3 ? dn[2 * hf] : (j > 3 ? dn[2 * hf + 1] : (q < 2 ? dn[2 * hf] : dn[2 * hf + 1]));
          op[i] = pack2(oacc[2 * i] * dv, oacc[2 * i + 1] * dv);
        }
      }
    SEND
  }
  STAMP(6);
  uint4* const psend = g_part + (mt * 8 + w8) * 7168 + lane;
  const uint4* const precv = g_part + (mt * 8 + s) * 7168 + lane;
  const int xo0 = (mt * 128 + s * 16 + (lane >> 2)) * DM + 2 * q;
  uint32_t gv[32], gx[4];
  #define G2_AB(ACC, T) \
    mbar_wait(fb + 8 * (T)); mbar_wait(fb + 8 * ((T) + 1)); wg_fence(); \
    wg_rs128<0, (dB128 + (buf_off(T) >> 4))>(ACC, op[0], op[1], op[2], op[3]); \
    wg_rs128<1, (dB128 + ((buf_off(T) + 2048) >> 4))>(ACC, op[4], op[5], op[6], op[7]); \
    wg_rs128<1, (dB128 + ((buf_off(T) + 4096) >> 4))>(ACC, op[8], op[9], op[10], op[11]); \
    wg_rs128<1, (dB128 + ((buf_off(T) + 6144) >> 4))>(ACC, op[12], op[13], 0u, 0u); \
    wg_rs128<1, (dB128h + (buf_off((T) + 1) >> 4))>(ACC, hp[0], hp[1], hp[2], hp[3]); \
    wg_rs128<1, (dB128h + ((buf_off((T) + 1) + 2048) >> 4))>(ACC, hp[4], hp[5], hp[6], hp[7]); \
    wg_commit(); wg_wait<1>();
  #define G2_H(ACC, T, H0) \
    mbar_wait(fb + 8 * (T)); wg_fence(); \
    SFOR(kk, 0, 4) \
      wg_rs128<1, (dB128 + ((buf_off(T) + kk * 2048) >> 4))>(ACC, hp[(H0) + 4 * kk], hp[(H0) + 4 * kk + 1], hp[(H0) + 4 * kk + 2], hp[(H0) + 4 * kk + 3]); \
    SEND \
    wg_commit(); wg_wait<1>();
  G2_AB(accB, 35);
  fence_regs<0, 64>(accA);
  mbar_arrive_pred(eb + 8 * 34, is0);
  geglu_slice<0, 7, 16, 40>(hp, accA, ca, cb);
  G2_H(accB, 37, 8);
  mbar_arrive_pred(eb + 8 * 35, is0); mbar_arrive_pred(eb + 8 * 36, is0);
  geglu_slice<7, 13, 16, 40>(hp, accA, ca, cb);
  G2_H(accB, 38, 24);
  mbar_arrive_pred(eb + 8 * 37, is0);
  geglu_slice<13, 16, 16, 40>(hp, accA, ca, cb);
  G2_H(accB, 39, 40);
  mbar_arrive_pred(eb + 8 * 38, is0);
  STAMP(7);
  G2_AB(accA, 40);
  fence_regs<0, 64>(accB);
  mbar_arrive_pred(eb + 8 * 39, is0);
  send_part<8>(accB, psend + s * 256, tag);
  G2_H(accA, 42, 8);
  G2_H(accA, 43, 24);
  G2_H(accA, 44, 40);
  STAMP(8);
  G2_AB(accB, 45);
  fence_regs<0, 64>(accA);
  send_part<8>(accA, psend + 2048 + s * 256, tag);
  gather4_issue(gv, precv + w8 * 32);
  resid4(gx, x, xo0 + 16 * w8);
  G2_H(accB, 47, 8);
  G2_H(accB, 48, 24);
  poll4(gv, precv + w8 * 32, tag);
  gather4_finish(gv, gx, out, xo0 + 16 * w8);
  G2_H(accB, 49, 40);
  gather4_issue(gv, precv + 2048 + w8 * 32);
  resid4(gx, x, xo0 + 128 + 16 * w8);
  STAMP(9);
  mbar_wait(fb + 8 * 50); wg_fence();
  wg_rs64<0, (dB128 + (buf_off(50) >> 4))>(accA, op[0], op[1], op[2], op[3]);
  wg_rs64<1, (dB128 + ((buf_off(50) + 2048) >> 4))>(accA, op[4], op[5], op[6], op[7]);
  wg_rs64<1, (dB128 + ((buf_off(50) + 4096) >> 4))>(accA, op[8], op[9], op[10], op[11]);
  wg_rs64<1, (dB128 + ((buf_off(50) + 6144) >> 4))>(accA, op[12], op[13], 0u, 0u);
  wg_rs64<1, (dB128 + ((buf_off(50) + 8192) >> 4))>(accA, hp[0], hp[1], hp[2], hp[3]);
  wg_rs64<1, (dB128 + ((buf_off(50) + 10240) >> 4))>(accA, hp[4], hp[5], hp[6], hp[7]);
  wg_commit();
  mbar_wait(fb + 8 * 51); mbar_wait(fb + 8 * 52); wg_fence();
  SFOR(kk, 0, 8)
    wg_rs64<1, (dB128 + ((buf_off(51) + kk * 2048) >> 4))>(accA, hp[8 + 4 * kk], hp[9 + 4 * kk], hp[10 + 4 * kk], hp[11 + 4 * kk]);
  SEND
  SFOR(kk, 0, 4)
    wg_rs64<1, (dB128 + ((buf_off(52) + kk * 2048) >> 4))>(accA, hp[40 + 4 * kk], hp[41 + 4 * kk], hp[42 + 4 * kk], hp[43 + 4 * kk]);
  SEND
  wg_commit();
  wg_wait<2>();
  fence_regs<0, 64>(accB);
  send_part<8>(accB, psend + 4096 + s * 256, tag);
  poll4(gv, precv + 2048 + w8 * 32, tag);
  gather4_finish(gv, gx, out, xo0 + 128 + 16 * w8);
  resid4(gx, x, xo0 + 256 + 16 * w8);
  const int xo3 = xo0 + 384 + 8 * w8;
  const uint32_t x30 = __ldg((const unsigned*)(x + xo3)), x31 = __ldg((const unsigned*)(x + xo3 + 8 * DM));
  wg_wait<0>();
  STAMP(10);
  fence_regs<0, 32>(accA);
  send_part<4>(accA, psend + 6144 + s * 128, tag);
  gather4_issue(gv, precv + 4096 + w8 * 32);
  uint32_t g3[16];
  const uint2* p3 = (const uint2*)(precv + 6144 + (w8 >> 1) * 32) + (w8 & 1);
  #pragma unroll
  for (int i = 0; i < 8; i++)
    asm volatile("ld.relaxed.gpu.global.v2.b32 {%0, %1}, [%2];" : "=r"(g3[2 * i]), "=r"(g3[2 * i + 1]) : "l"(p3 + i * 256) : "memory");
  poll4(gv, precv + 4096 + w8 * 32, tag);
  gather4_finish(gv, gx, out, xo0 + 256 + 16 * w8);
  STAMP(11);
  poll2(g3, p3, tag);
  {
    float a0 = bf_lo(x30), a1 = bf_hi(x30), a2 = bf_lo(x31), a3 = bf_hi(x31);
    #pragma unroll
    for (int i = 0; i < 8; i++) { a0 += untag_lo(g3[2 * i]); a1 += bf_hi(g3[2 * i]); a2 += bf_lo(g3[2 * i + 1]); a3 += bf_hi(g3[2 * i + 1]); }
    *(unsigned*)(out + xo3) = pack2(a0, a1); *(unsigned*)(out + xo3 + 8 * DM) = pack2(a2, a3);
  }
  STAMP(12);
}

typedef CUresult (*PFN_enc)(CUtensorMap*, CUtensorMapDataType, cuuint32_t, void*, const cuuint64_t*, const cuuint64_t*, const cuuint32_t*, const cuuint32_t*,
                            CUtensorMapInterleave, CUtensorMapSwizzle, CUtensorMapL2promotion, CUtensorMapFloatOOBfill);
void enc2d(PFN_enc enc, CUtensorMap* m, const void* base, uint64_t inner, uint64_t outer, uint32_t bi, uint32_t bo, CUtensorMapSwizzle sw) {
  cuuint64_t dims[2] = {inner, outer}; cuuint64_t strides[1] = {inner * 2};
  cuuint32_t box[2] = {bi, bo}; cuuint32_t es[2] = {1, 1};
  enc(m, CU_TENSOR_MAP_DATA_TYPE_BFLOAT16, 2, const_cast<void*>(base), dims, strides, box, es, CU_TENSOR_MAP_INTERLEAVE_NONE, sw,
      CU_TENSOR_MAP_L2_PROMOTION_L2_128B, CU_TENSOR_MAP_FLOAT_OOB_FILL_NONE);
}

}

extern "C" void kernel_launch(void* const* d_in, const int* in_sizes, int n_in, void* d_out, int out_size) {
  static PFN_enc enc = nullptr;
  if (!enc) {
    void* fn = nullptr; cudaDriverEntryPointQueryResult qr;
    cudaGetDriverEntryPoint("cuTensorMapEncodeTiled", &fn, cudaEnableDefault, &qr);
    enc = (PFN_enc)fn;
    cudaFuncSetAttribute(fused_kernel, cudaFuncAttributeMaxDynamicSharedMemorySize, SMEM_BYTES);
  }
  Maps mp;
  const CUtensorMapSwizzle S128 = CU_TENSOR_MAP_SWIZZLE_128B, S64 = CU_TENSOR_MAP_SWIZZLE_64B;
  enc2d(enc, &mp.x, d_in[0], 448, 2048, 64, 128, S128);
  enc2d(enc, &mp.qkv, d_in[1], 1344, 448, 64, 64, S128);
  enc2d(enc, &mp.q64, d_in[1], 1344, 448, 32, 64, S64);
  enc2d(enc, &mp.g, d_in[4], 1792, 448, 64, 64, S128);
  enc2d(enc, &mp.u, d_in[5], 1792, 448, 64, 64, S128);
  enc2d(enc, &mp.g64, d_in[4], 1792, 448, 32, 64, S64);
  enc2d(enc, &mp.u64, d_in[5], 1792, 448, 32, 64, S64);
  enc2d(enc, &mp.d, d_in[6], 448, 1792, 64, 64, S128);
  enc2d(enc, &mp.d32, d_in[6], 448, 1792, 64, 32, S128);
  enc2d(enc, &mp.o, d_in[2], 448, 448, 64, 64, S128);
  fused_kernel<<<128, 384, SMEM_BYTES>>>(mp, (const __nv_bfloat16*)d_in[0], (__nv_bfloat16*)d_out);
}
```

```cpp
#include <cuda_runtime.h>
#include <cuda.h>
#include <cuda_bf16.h>
#include <stdint.h>

#define WDELAY 2
#define W0POS 6
#define PFM 2
#define NRS 3
#define XWAIT 4
namespace {

constexpr int DM = 448;
constexpr uint32_t SB = 0x400;
constexpr uint32_t OFF_X = 0;
constexpr uint32_t OFF_SLOT = 7 * 16384;
constexpr uint32_t OFF_BAR = 14 * 16384;
constexpr uint32_t BAR_FULL = OFF_BAR;
constexpr uint32_t BAR_EMPTY = OFF_BAR + 512;
constexpr uint32_t BAR_X = OFF_BAR + 1024;
constexpr uint32_t BAR_XW = OFF_BAR + 1080;
constexpr uint32_t BAR_XR = OFF_BAR + 1088;
constexpr uint32_t BAR_TW = OFF_BAR + 1096;
constexpr uint32_t BAR_TILES = OFF_BAR + 1104;
constexpr uint32_t BAR_KVP = OFF_BAR + 1112;
constexpr uint32_t BAR_KVB = OFF_BAR + 1128;
constexpr uint32_t BAR_PAR = OFF_BAR + 1136;
constexpr uint32_t OFF_PAR = OFF_BAR + 1144;
constexpr uint32_t BAR_RDY = OFF_BAR + 1152;
constexpr uint32_t BAR_DAT = OFF_BAR + 1216;
constexpr uint32_t BAR_OW = OFF_BAR + 1472;
#define SMEM_BYTES (OFF_BAR + 1536 + TSB)
constexpr uint32_t OFF_KVB = OFF_SLOT + 6 * 16384 + 8192;
constexpr uint32_t BAR_RDY2 = OFF_BAR + 1016;
constexpr int KVN = 21 * 128;

__device__ float g_kvsum[2 * 8 * KVN];
__device__ unsigned g_cnt[8 * 32];
__device__ unsigned g_cnt2[16 * 32];
#define STAMP(i)
#define STAMPW(i)
#define GSTAMP(v)
#define TSB 0

struct Maps { CUtensorMap x, qkv, q32, q24, g32, u32, g, u, d, d32, o, out; };

__host__ __device__ constexpr uint32_t buf_off(int t) {
  if (t < 7) return OFF_SLOT + (t == 4 ? 5 : (t == 5 ? 4 : t)) * 16384;
  if (t < 12) return OFF_SLOT + (t == 11 ? 5 : t - 7) * 16384;
  if (t < 35) return OFF_SLOT + ((t - 12) % 6) * 16384;
  constexpr int tb[18] = {0, 26, 2, 24, 8, 10, 4, 27, 14, 22, 16, 18, 20, 0, 23, 2, 24, 4};
  return tb[t - 35] * 8192;
}
__host__ __device__ constexpr int ord_of(int i) { constexpr int tb[18] = {36, 35, 37, 38, 41, 39, 42, 40, 43, 45, 46, 47, 44, 49, 48, 50, 51, 52}; return tb[i]; }
__host__ __device__ constexpr int dep_of(int i) { constexpr int tb[18] = {0, 0, 29, 30, 31, 32, 0, 33, 0, 0, 0, 0, 34, 0, 37, 0, 41, 0}; return tb[i]; }

__device__ __forceinline__ uint32_t smem_u32(const void* p) { return (uint32_t)__cvta_generic_to_shared(p); }
__device__ __forceinline__ void mbar_init(uint32_t bar, uint32_t cnt) { asm volatile("mbarrier.init.shared::cta.b64 [%0], %1;" :: "r"(bar), "r"(cnt) : "memory"); }
__device__ __forceinline__ void mbar_expect_tx(uint32_t bar, uint32_t bytes) { asm volatile("mbarrier.arrive.expect_tx.shared::cta.b64 _, [%0], %1;" :: "r"(bar), "r"(bytes) : "memory"); }
__device__ __forceinline__ void mbar_arrive(uint32_t bar) { asm volatile("mbarrier.arrive.shared::cta.b64 _, [%0];" :: "r"(bar) : "memory"); }
__device__ __forceinline__ void mbar_arrive_pred(uint32_t bar, uint32_t pred) {
  asm volatile("{\n.reg .pred p;\nsetp.ne.u32 p, %1, 0;\n@p mbarrier.arrive.shared::cta.b64 _, [%0];\n}" :: "r"(bar), "r"(pred) : "memory");
}
__device__ __forceinline__ void mbar_wait_(uint32_t bar, uint32_t& budget) {
  asm volatile("{\n.reg .pred P1;\nLAB_WAIT:\n"
    "mbarrier.try_wait.parity.shared::cta.b64 P1, [%1], 0;\n"
    "add.u32 %0, %0, 1;\nsetp.lt.and.u32 P1, %0, 8000000, !P1;\n@P1 bra LAB_WAIT;\n}\n" : "+r"(budget) : "r"(bar) : "memory");
}
#define mbar_wait(bar) mbar_wait_(bar, budget)
__device__ __forceinline__ void tma2d(uint32_t dst, const CUtensorMap* m, uint32_t bar, int c0, int c1) {
  asm volatile("cp.async.bulk.tensor.2d.shared::cluster.global.mbarrier::complete_tx::bytes [%0], [%1, {%3, %4}], [%2];"
    :: "r"(dst), "l"(m), "r"(bar), "r"(c0), "r"(c1) : "memory");
}
__device__ __forceinline__ uint32_t elect_one() {
  uint32_t p; asm volatile("{\n.reg .pred P;\nelect.sync _|P, 0xffffffff;\nselp.u32 %0, 1, 0, P;\n}" : "=r"(p)); return p;
}
__device__ __forceinline__ int lane_id() { int l; asm volatile("mov.u32 %0, %%laneid;" : "=r"(l)); return l; }
__device__ __forceinline__ void prefetch_map(const CUtensorMap* m) { asm volatile("prefetch.tensormap [%0];" :: "l"(m) : "memory"); }
__device__ __forceinline__ void fence_async() { asm volatile("fence.proxy.async.shared::cta;" ::: "memory"); }
__device__ __forceinline__ void wg_fence() { asm volatile("wgmma.fence.sync.aligned;" ::: "memory"); }
__device__ __forceinline__ void wg_commit() { asm volatile("wgmma.commit_group.sync.aligned;" ::: "memory"); }
template<int N> __device__ __forceinline__ void wg_wait() { asm volatile("wgmma.wait_group.sync.aligned %0;" :: "n"(N) : "memory"); }
__host__ __device__ constexpr uint64_t make_desc(uint32_t addr, uint32_t lbo, uint32_t sbo, uint64_t swz) {
  return (uint64_t)((addr & 0x3FFFF) >> 4) | ((uint64_t)(lbo >> 4) << 16) | ((uint64_t)(sbo >> 4) << 32) | (swz << 62);
}
template<int LO, int HI, int N> __device__ __forceinline__ void fence_regs(float (&a)[N]) {
  #pragma unroll
  for (int i = LO; i < HI; i++) asm volatile("" : "+f"(a[i]) :: "memory");
}
__device__ __forceinline__ uint32_t pack2(float lo, float hi) { uint32_t r; asm("cvt.rn.bf16x2.f32 %0, %1, %2;" : "=r"(r) : "f"(hi), "f"(lo)); return r; }
__device__ __forceinline__ void ldsm4(uint32_t& a, uint32_t& b, uint32_t& c, uint32_t& d, uint32_t addr) {
  asm volatile("ldmatrix.sync.aligned.m8n8.x4.shared.b16 {%0, %1, %2, %3}, [%4];" : "=r"(a), "=r"(b), "=r"(c), "=r"(d) : "r"(addr) : "memory");
}
__device__ __forceinline__ void stsm4(uint32_t addr, uint32_t a, uint32_t b, uint32_t c, uint32_t d) {
  asm volatile("stmatrix.sync.aligned.m8n8.x4.shared.b16 [%0], {%1, %2, %3, %4};" :: "r"(addr), "r"(a), "r"(b), "r"(c), "r"(d) : "memory");
}
__device__ __forceinline__ void mma_rowsum(float (&c)[4], uint32_t a0, uint32_t a1, uint32_t a2, uint32_t a3) {
  asm volatile("mma.sync.aligned.m16n8k16.row.col.f32.bf16.bf16.f32 {%0,%1,%2,%3}, {%4,%5,%6,%7}, {%8,%8}, {%0,%1,%2,%3};"
    : "+f"(c[0]), "+f"(c[1]), "+f"(c[2]), "+f"(c[3]) : "r"(a0), "r"(a1), "r"(a2), "r"(a3), "r"(0x3F803F80u));
}
__device__ __forceinline__ uint32_t hsub2(uint32_t a, uint32_t b) { uint32_t r; asm("sub.rn.bf16x2 %0, %1, %2;" : "=r"(r) : "r"(a), "r"(b)); return r; }
__device__ __forceinline__ uint32_t hadd2(uint32_t a, uint32_t b) { uint32_t r; asm("add.rn.bf16x2 %0, %1, %2;" : "=r"(r) : "r"(a), "r"(b)); return r; }
__device__ __forceinline__ uint32_t hfma2(uint32_t a, uint32_t b, uint32_t c) { uint32_t r; asm("fma.rn.bf16x2 %0, %1, %2, %3;" : "=r"(r) : "r"(a), "r"(b), "r"(c)); return r; }
__device__ __forceinline__ void warp_arrive(uint32_t bar) {
  __syncwarp();
  asm volatile("{\n.reg .pred p;\nelect.sync _|p, 0xffffffff;\n@p mbarrier.arrive.shared::cta.b64 _, [%0];\n}" :: "r"(bar) : "memory");
}
__device__ __forceinline__ float bf_lo(uint32_t u) { return __uint_as_float(u << 16); }
__device__ __forceinline__ float bf_hi(uint32_t u) { return __uint_as_float(u & 0xFFFF0000u); }
__device__ __forceinline__ float bf_round(float x) { return bf_lo(pack2(x, 0.f)); }
__device__ __forceinline__ float ex2(float x) { float r; asm("ex2.approx.ftz.f32 %0, %1;" : "=f"(r) : "f"(x)); return r; }
__device__ __forceinline__ float rcp(float x) { float r; asm("rcp.approx.ftz.f32 %0, %1;" : "=f"(r) : "f"(x)); return r; }
__device__ __forceinline__ float sqrt_approx(float x) { float r; asm("sqrt.approx.ftz.f32 %0, %1;" : "=f"(r) : "f"(x)); return r; }
__device__ __forceinline__ uint32_t phi2(float a0, float a1, float r, float rl) {
  float e0 = ex2(a0 * rl) + 1e-6f, e1 = ex2(a1 * rl) + 1e-6f;
  float p0 = a0 > 0.f ? fmaf(a0, r, 1.000001f) : e0;
  float p1 = a1 > 0.f ? fmaf(a1, r, 1.000001f) : e1;
  return pack2(p0, p1);
}
__device__ __forceinline__ float geglu1(float g, float u, float c0, float c1, float c2) {
  float t = fmaf(g * g, c1, c0) * g, th;
  asm("tanh.approx.f32 %0, %1;" : "=f"(th) : "f"(t));
  float hh = g * u * c2;
  return fmaf(hh, th, hh);
}

template<int SD, uint64_t AD, uint64_t BD, int SZ> __device__ __forceinline__ void wg_ss128(float (&d)[SZ], uint32_t aoff) {
  if constexpr (SD == 0)
  asm volatile("{\n.reg .pred p;\n.reg .b64 ad, bd;\n.reg .b32 lo;\nsetp.ne.b32 p, 0, 0;\n"
    "add.u32 lo, %64, %65;\nmov.b64 ad, {lo, %66};\n"
    "mov.b64 bd, %67;\n"
    "wgmma.mma_async.sync.aligned.m64n128k16.f32.bf16.bf16 "
    "{%0, %1, %2, %3, %4, %5, %6, %7, %8, %9, %10, %11, %12, %13, %14, %15, %16, %17, %18, %19, %20, %21, %22, %23, %24, %25, %26, %27, %28, %29, %30, %31, %32, %33, %34, %35, %36, %37, %38, %39, %40, %41, %42, %43, %44, %45, %46, %47, %48, %49, %50, %51, %52, %53, %54, %55, %56, %57, %58, %59, %60, %61, %62, %63}, "
    "ad, bd, p, 1, 1, 0, 1;\n}\n"
    : "=f"(d[0]), "=f"(d[1]), "=f"(d[2]), "=f"(d[3]), "=f"(d[4]), "=f"(d[5]), "=f"(d[6]), "=f"(d[7]), "=f"(d[8]), "=f"(d[9]), "=f"(d[10]), "=f"(d[11]), "=f"(d[12]), "=f"(d[13]), "=f"(d[14]), "=f"(d[15]), "=f"(d[16]), "=f"(d[17]), "=f"(d[18]), "=f"(d[19]), "=f"(d[20]), "=f"(d[21]), "=f"(d[22]), "=f"(d[23]), "=f"(d[24]), "=f"(d[25]), "=f"(d[26]), "=f"(d[27]), "=f"(d[28]), "=f"(d[29]), "=f"(d[30]), "=f"(d[31]), "=f"(d[32]), "=f"(d[33]), "=f"(d[34]), "=f"(d[35]), "=f"(d[36]), "=f"(d[37]), "=f"(d[38]), "=f"(d[39]), "=f"(d[40]), "=f"(d[41]), "=f"(d[42]), "=f"(d[43]), "=f"(d[44]), "=f"(d[45]), "=f"(d[46]), "=f"(d[47]), "=f"(d[48]), "=f"(d[49]), "=f"(d[50]), "=f"(d[51]), "=f"(d[52]), "=f"(d[53]), "=f"(d[54]), "=f"(d[55]), "=f"(d[56]), "=f"(d[57]), "=f"(d[58]), "=f"(d[59]), "=f"(d[60]), "=f"(d[61]), "=f"(d[62]), "=f"(d[63])
    : "r"(aoff), "n"((uint32_t)AD), "n"((uint32_t)(AD >> 32)), "n"(BD));
  if constexpr (SD == 1)
  asm volatile("{\n.reg .pred p;\n.reg .b64 ad, bd;\n.reg .b32 lo;\nsetp.ne.b32 p, 1, 0;\n"
    "add.u32 lo, %64, %65;\nmov.b64 ad, {lo, %66};\n"
    "mov.b64 bd, %67;\n"
    "wgmma.mma_async.sync.aligned.m64n128k16.f32.bf16.bf16 "
    "{%0, %1, %2, %3, %4, %5, %6, %7, %8, %9, %10, %11, %12, %13, %14, %15, %16, %17, %18, %19, %20, %21, %22, %23, %24, %25, %26, %27, %28, %29, %30, %31, %32, %33, %34, %35, %36, %37, %38, %39, %40, %41, %42, %43, %44, %45, %46, %47, %48, %49, %50, %51, %52, %53, %54, %55, %56, %57, %58, %59, %60, %61, %62, %63}, "
    "ad, bd, p, 1, 1, 0, 1;\n}\n"
    : "+f"(d[0]), "+f"(d[1]), "+f"(d[2]), "+f"(d[3]), "+f"(d[4]), "+f"(d[5]), "+f"(d[6]), "+f"(d[7]), "+f"(d[8]), "+f"(d[9]), "+f"(d[10]), "+f"(d[11]), "+f"(d[12]), "+f"(d[13]), "+f"(d[14]), "+f"(d[15]), "+f"(d[16]), "+f"(d[17]), "+f"(d[18]), "+f"(d[19]), "+f"(d[20]), "+f"(d[21]), "+f"(d[22]), "+f"(d[23]), "+f"(d[24]), "+f"(d[25]), "+f"(d[26]), "+f"(d[27]), "+f"(d[28]), "+f"(d[29]), "+f"(d[30]), "+f"(d[31]), "+f"(d[32]), "+f"(d[33]), "+f"(d[34]), "+f"(d[35]), "+f"(d[36]), "+f"(d[37]), "+f"(d[38]), "+f"(d[39]), "+f"(d[40]), "+f"(d[41]), "+f"(d[42]), "+f"(d[43]), "+f"(d[44]), "+f"(d[45]), "+f"(d[46]), "+f"(d[47]), "+f"(d[48]), "+f"(d[49]), "+f"(d[50]), "+f"(d[51]), "+f"(d[52]), "+f"(d[53]), "+f"(d[54]), "+f"(d[55]), "+f"(d[56]), "+f"(d[57]), "+f"(d[58]), "+f"(d[59]), "+f"(d[60]), "+f"(d[61]), "+f"(d[62]), "+f"(d[63])
    : "r"(aoff), "n"((uint32_t)AD), "n"((uint32_t)(AD >> 32)), "n"(BD));
}
template<int SD, uint64_t AD, uint64_t BD, int SZ> __device__ __forceinline__ void wg_ss120(float (&d)[SZ], uint32_t aoff) {
  if constexpr (SD == 0)
  asm volatile("{\n.reg .pred p;\n.reg .b64 ad, bd;\n.reg .b32 lo;\nsetp.ne.b32 p, 0, 0;\n"
    "add.u32 lo, %60, %61;\nmov.b64 ad, {lo, %62};\n"
    "mov.b64 bd, %63;\n"
    "wgmma.mma_async.sync.aligned.m64n120k16.f32.bf16.bf16 "
    "{%0, %1, %2, %3, %4, %5, %6, %7, %8, %9, %10, %11, %12, %13, %14, %15, %16, %17, %18, %19, %20, %21, %22, %23, %24, %25, %26, %27, %28, %29, %30, %31, %32, %33, %34, %35, %36, %37, %38, %39, %40, %41, %42, %43, %44, %45, %46, %47, %48, %49, %50, %51, %52, %53, %54, %55, %56, %57, %58, %59}, "
    "ad, bd, p, 1, 1, 0, 1;\n}\n"
    : "=f"(d[0]), "=f"(d[1]), "=f"(d[2]), "=f"(d[3]), "=f"(d[4]), "=f"(d[5]), "=f"(d[6]), "=f"(d[7]), "=f"(d[8]), "=f"(d[9]), "=f"(d[10]), "=f"(d[11]), "=f"(d[12]), "=f"(d[13]), "=f"(d[14]), "=f"(d[15]), "=f"(d[16]), "=f"(d[17]), "=f"(d[18]), "=f"(d[19]), "=f"(d[20]), "=f"(d[21]), "=f"(d[22]), "=f"(d[23]), "=f"(d[24]), "=f"(d[25]), "=f"(d[26]), "=f"(d[27]), "=f"(d[28]), "=f"(d[29]), "=f"(d[30]), "=f"(d[31]), "=f"(d[32]), "=f"(d[33]), "=f"(d[34]), "=f"(d[35]), "=f"(d[36]), "=f"(d[37]), "=f"(d[38]), "=f"(d[39]), "=f"(d[40]), "=f"(d[41]), "=f"(d[42]), "=f"(d[43]), "=f"(d[44]), "=f"(d[45]), "=f"(d[46]), "=f"(d[47]), "=f"(d[48]), "=f"(d[49]), "=f"(d[50]), "=f"(d[51]), "=f"(d[52]), "=f"(d[53]), "=f"(d[54]), "=f"(d[55]), "=f"(d[56]), "=f"(d[57]), "=f"(d[58]), "=f"(d[59])
    : "r"(aoff), "n"((uint32_t)AD), "n"((uint32_t)(AD >> 32)), "n"(BD));
  if constexpr (SD == 1)
  asm volatile("{\n.reg .pred p;\n.reg .b64 ad, bd;\n.reg .b32 lo;\nsetp.ne.b32 p, 1, 0;\n"
    "add.u32 lo, %60, %61;\nmov.b64 ad, {lo, %62};\n"
    "mov.b64 bd, %63;\n"
    "wgmma.mma_async.sync.aligned.m64n120k16.f32.bf16.bf16 "
    "{%0, %1, %2, %3, %4, %5, %6, %7, %8, %9, %10, %11, %12, %13, %14, %15, %16, %17, %18, %19, %20, %21, %22, %23, %24, %25, %26, %27, %28, %29, %30, %31, %32, %33, %34, %35, %36, %37, %38, %39, %40, %41, %42, %43, %44, %45, %46, %47, %48, %49, %50, %51, %52, %53, %54, %55, %56, %57, %58, %59}, "
    "ad, bd, p, 1, 1, 0, 1;\n}\n"
    : "+f"(d[0]), "+f"(d[1]), "+f"(d[2]), "+f"(d[3]), "+f"(d[4]), "+f"(d[5]), "+f"(d[6]), "+f"(d[7]), "+f"(d[8]), "+f"(d[9]), "+f"(d[10]), "+f"(d[11]), "+f"(d[12]), "+f"(d[13]), "+f"(d[14]), "+f"(d[15]), "+f"(d[16]), "+f"(d[17]), "+f"(d[18]), "+f"(d[19]), "+f"(d[20]), "+f"(d[21]), "+f"(d[22]), "+f"(d[23]), "+f"(d[24]), "+f"(d[25]), "+f"(d[26]), "+f"(d[27]), "+f"(d[28]), "+f"(d[29]), "+f"(d[30]), "+f"(d[31]), "+f"(d[32]), "+f"(d[33]), "+f"(d[34]), "+f"(d[35]), "+f"(d[36]), "+f"(d[37]), "+f"(d[38]), "+f"(d[39]), "+f"(d[40]), "+f"(d[41]), "+f"(d[42]), "+f"(d[43]), "+f"(d[44]), "+f"(d[45]), "+f"(d[46]), "+f"(d[47]), "+f"(d[48]), "+f"(d[49]), "+f"(d[50]), "+f"(d[51]), "+f"(d[52]), "+f"(d[53]), "+f"(d[54]), "+f"(d[55]), "+f"(d[56]), "+f"(d[57]), "+f"(d[58]), "+f"(d[59])
    : "r"(aoff), "n"((uint32_t)AD), "n"((uint32_t)(AD >> 32)), "n"(BD));
}
template<int SD, uint64_t AD, uint64_t BD, int SZ> __device__ __forceinline__ void wg_ss40t(float (&d)[SZ], uint32_t aoff) {
  if constexpr (SD == 0)
  asm volatile("{\n.reg .pred p;\n.reg .b64 ad, bd;\n.reg .b32 lo;\nsetp.ne.b32 p, 0, 0;\n"
    "mov.u32 lo, %21;\nmov.b64 ad, {lo, %22};\n"
    "add.u32 lo, %20, %23;\nmov.b64 bd, {lo, %24};\n"
    "wgmma.mma_async.sync.aligned.m64n40k16.f32.bf16.bf16 "
    "{%0, %1, %2, %3, %4, %5, %6, %7, %8, %9, %10, %11, %12, %13, %14, %15, %16, %17, %18, %19}, "
    "ad, bd, p, 1, 1, 1, 1;\n}\n"
    : "=f"(d[0]), "=f"(d[1]), "=f"(d[2]), "=f"(d[3]), "=f"(d[4]), "=f"(d[5]), "=f"(d[6]), "=f"(d[7]), "=f"(d[8]), "=f"(d[9]), "=f"(d[10]), "=f"(d[11]), "=f"(d[12]), "=f"(d[13]), "=f"(d[14]), "=f"(d[15]), "=f"(d[16]), "=f"(d[17]), "=f"(d[18]), "=f"(d[19])
    : "r"(aoff), "n"((uint32_t)AD), "n"((uint32_t)(AD >> 32)), "n"((uint32_t)BD), "n"((uint32_t)(BD >> 32)));
  if constexpr (SD == 1)
  asm volatile("{\n.reg .pred p;\n.reg .b64 ad, bd;\n.reg .b32 lo;\nsetp.ne.b32 p, 1, 0;\n"
    "mov.u32 lo, %21;\nmov.b64 ad, {lo, %22};\n"
    "add.u32 lo, %20, %23;\nmov.b64 bd, {lo, %24};\n"
    "wgmma.mma_async.sync.aligned.m64n40k16.f32.bf16.bf16 "
    "{%0, %1, %2, %3, %4, %5, %6, %7, %8, %9, %10, %11, %12, %13, %14, %15, %16, %17, %18, %19}, "
    "ad, bd, p, 1, 1, 1, 1;\n}\n"
    : "+f"(d[0]), "+f"(d[1]), "+f"(d[2]), "+f"(d[3]), "+f"(d[4]), "+f"(d[5]), "+f"(d[6]), "+f"(d[7]), "+f"(d[8]), "+f"(d[9]), "+f"(d[10]), "+f"(d[11]), "+f"(d[12]), "+f"(d[13]), "+f"(d[14]), "+f"(d[15]), "+f"(d[16]), "+f"(d[17]), "+f"(d[18]), "+f"(d[19])
    : "r"(aoff), "n"((uint32_t)AD), "n"((uint32_t)(AD >> 32)), "n"((uint32_t)BD), "n"((uint32_t)(BD >> 32)));
}
template<int SD, uint64_t BD, int SZ> __device__ __forceinline__ void wg_rs128(float (&d)[SZ], uint32_t a0, uint32_t a1, uint32_t a2, uint32_t a3) {
  if constexpr (SD == 0)
  asm volatile("{\n.reg .pred p;\n.reg .b64 ad, bd;\n.reg .b32 lo;\nsetp.ne.b32 p, 0, 0;\n"
    "mov.b64 bd, %68;\n"
    "wgmma.mma_async.sync.aligned.m64n128k16.f32.bf16.bf16 "
    "{%0, %1, %2, %3, %4, %5, %6, %7, %8, %9, %10, %11, %12, %13, %14, %15, %16, %17, %18, %19, %20, %21, %22, %23, %24, %25, %26, %27, %28, %29, %30, %31, %32, %33, %34, %35, %36, %37, %38, %39, %40, %41, %42, %43, %44, %45, %46, %47, %48, %49, %50, %51, %52, %53, %54, %55, %56, %57, %58, %59, %60, %61, %62, %63}, "
    "{%64, %65, %66, %67}, bd, p, 1, 1, 1;\n}\n"
    : "=f"(d[0]), "=f"(d[1]), "=f"(d[2]), "=f"(d[3]), "=f"(d[4]), "=f"(d[5]), "=f"(d[6]), "=f"(d[7]), "=f"(d[8]), "=f"(d[9]), "=f"(d[10]), "=f"(d[11]), "=f"(d[12]), "=f"(d[13]), "=f"(d[14]), "=f"(d[15]), "=f"(d[16]), "=f"(d[17]), "=f"(d[18]), "=f"(d[19]), "=f"(d[20]), "=f"(d[21]), "=f"(d[22]), "=f"(d[23]), "=f"(d[24]), "=f"(d[25]), "=f"(d[26]), "=f"(d[27]), "=f"(d[28]), "=f"(d[29]), "=f"(d[30]), "=f"(d[31]), "=f"(d[32]), "=f"(d[33]), "=f"(d[34]), "=f"(d[35]), "=f"(d[36]), "=f"(d[37]), "=f"(d[38]), "=f"(d[39]), "=f"(d[40]), "=f"(d[41]), "=f"(d[42]), "=f"(d[43]), "=f"(d[44]), "=f"(d[45]), "=f"(d[46]), "=f"(d[47]), "=f"(d[48]), "=f"(d[49]), "=f"(d[50]), "=f"(d[51]), "=f"(d[52]), "=f"(d[53]), "=f"(d[54]), "=f"(d[55]), "=f"(d[56]), "=f"(d[57]), "=f"(d[58]), "=f"(d[59]), "=f"(d[60]), "=f"(d[61]), "=f"(d[62]), "=f"(d[63])
    : "r"(a0), "r"(a1), "r"(a2), "r"(a3), "n"(BD));
  if constexpr (SD == 1)
  asm volatile("{\n.reg .pred p;\n.reg .b64 ad, bd;\n.reg .b32 lo;\nsetp.ne.b32 p, 1, 0;\n"
    "mov.b64 bd, %68;\n"
    "wgmma.mma_async.sync.aligned.m64n128k16.f32.bf16.bf16 "
    "{%0, %1, %2, %3, %4, %5, %6, %7, %8, %9, %10, %11, %12, %13, %14, %15, %16, %17, %18, %19, %20, %21, %22, %23, %24, %25, %26, %27, %28, %29, %30, %31, %32, %33, %34, %35, %36, %37, %38, %39, %40, %41, %42, %43, %44, %45, %46, %47, %48, %49, %50, %51, %52, %53, %54, %55, %56, %57, %58, %59, %60, %61, %62, %63}, "
    "{%64, %65, %66, %67}, bd, p, 1, 1, 1;\n}\n"
    : "+f"(d[0]), "+f"(d[1]), "+f"(d[2]), "+f"(d[3]), "+f"(d[4]), "+f"(d[5]), "+f"(d[6]), "+f"(d[7]), "+f"(d[8]), "+f"(d[9]), "+f"(d[10]), "+f"(d[11]), "+f"(d[12]), "+f"(d[13]), "+f"(d[14]), "+f"(d[15]), "+f"(d[16]), "+f"(d[17]), "+f"(d[18]), "+f"(d[19]), "+f"(d[20]), "+f"(d[21]), "+f"(d[22]), "+f"(d[23]), "+f"(d[24]), "+f"(d[25]), "+f"(d[26]), "+f"(d[27]), "+f"(d[28]), "+f"(d[29]), "+f"(d[30]), "+f"(d[31]), "+f"(d[32]), "+f"(d[33]), "+f"(d[34]), "+f"(d[35]), "+f"(d[36]), "+f"(d[37]), "+f"(d[38]), "+f"(d[39]), "+f"(d[40]), "+f"(d[41]), "+f"(d[42]), "+f"(d[43]), "+f"(d[44]), "+f"(d[45]), "+f"(d[46]), "+f"(d[47]), "+f"(d[48]), "+f"(d[49]), "+f"(d[50]), "+f"(d[51]), "+f"(d[52]), "+f"(d[53]), "+f"(d[54]), "+f"(d[55]), "+f"(d[56]), "+f"(d[57]), "+f"(d[58]), "+f"(d[59]), "+f"(d[60]), "+f"(d[61]), "+f"(d[62]), "+f"(d[63])
    : "r"(a0), "r"(a1), "r"(a2), "r"(a3), "n"(BD));
}
template<int SD, uint64_t BD, int SZ> __device__ __forceinline__ void wg_rs120(float (&d)[SZ], uint32_t a0, uint32_t a1, uint32_t a2, uint32_t a3, uint32_t boff) {
  if constexpr (SD == 0)
  asm volatile("{\n.reg .pred p;\n.reg .b64 ad, bd;\n.reg .b32 lo;\nsetp.ne.b32 p, 0, 0;\n"
    "add.u32 lo, %64, %65;\nmov.b64 bd, {lo, %66};\n"
    "wgmma.mma_async.sync.aligned.m64n120k16.f32.bf16.bf16 "
    "{%0, %1, %2, %3, %4, %5, %6, %7, %8, %9, %10, %11, %12, %13, %14, %15, %16, %17, %18, %19, %20, %21, %22, %23, %24, %25, %26, %27, %28, %29, %30, %31, %32, %33, %34, %35, %36, %37, %38, %39, %40, %41, %42, %43, %44, %45, %46, %47, %48, %49, %50, %51, %52, %53, %54, %55, %56, %57, %58, %59}, "
    "{%60, %61, %62, %63}, bd, p, 1, 1, 1;\n}\n"
    : "=f"(d[0]), "=f"(d[1]), "=f"(d[2]), "=f"(d[3]), "=f"(d[4]), "=f"(d[5]), "=f"(d[6]), "=f"(d[7]), "=f"(d[8]), "=f"(d[9]), "=f"(d[10]), "=f"(d[11]), "=f"(d[12]), "=f"(d[13]), "=f"(d[14]), "=f"(d[15]), "=f"(d[16]), "=f"(d[17]), "=f"(d[18]), "=f"(d[19]), "=f"(d[20]), "=f"(d[21]), "=f"(d[22]), "=f"(d[23]), "=f"(d[24]), "=f"(d[25]), "=f"(d[26]), "=f"(d[27]), "=f"(d[28]), "=f"(d[29]), "=f"(d[30]), "=f"(d[31]), "=f"(d[32]), "=f"(d[33]), "=f"(d[34]), "=f"(d[35]), "=f"(d[36]), "=f"(d[37]), "=f"(d[38]), "=f"(d[39]), "=f"(d[40]), "=f"(d[41]), "=f"(d[42]), "=f"(d[43]), "=f"(d[44]), "=f"(d[45]), "=f"(d[46]), "=f"(d[47]), "=f"(d[48]), "=f"(d[49]), "=f"(d[50]), "=f"(d[51]), "=f"(d[52]), "=f"(d[53]), "=f"(d[54]), "=f"(d[55]), "=f"(d[56]), "=f"(d[57]), "=f"(d[58]), "=f"(d[59])
    : "r"(a0), "r"(a1), "r"(a2), "r"(a3), "r"(boff), "n"((uint32_t)BD), "n"((uint32_t)(BD >> 32)));
  if constexpr (SD == 1)
  asm volatile("{\n.reg .pred p;\n.reg .b64 ad, bd;\n.reg .b32 lo;\nsetp.ne.b32 p, 1, 0;\n"
    "add.u32 lo, %64, %65;\nmov.b64 bd, {lo, %66};\n"
    "wgmma.mma_async.sync.aligned.m64n120k16.f32.bf16.bf16 "
    "{%0, %1, %2, %3, %4, %5, %6, %7, %8, %9, %10, %11, %12, %13, %14, %15, %16, %17, %18, %19, %20, %21, %22, %23, %24, %25, %26, %27, %28, %29, %30, %31, %32, %33, %34, %35, %36, %37, %38, %39, %40, %41, %42, %43, %44, %45, %46, %47, %48, %49, %50, %51, %52, %53, %54, %55, %56, %57, %58, %59}, "
    "{%60, %61, %62, %63}, bd, p, 1, 1, 1;\n}\n"
    : "+f"(d[0]), "+f"(d[1]), "+f"(d[2]), "+f"(d[3]), "+f"(d[4]), "+f"(d[5]), "+f"(d[6]), "+f"(d[7]), "+f"(d[8]), "+f"(d[9]), "+f"(d[10]), "+f"(d[11]), "+f"(d[12]), "+f"(d[13]), "+f"(d[14]), "+f"(d[15]), "+f"(d[16]), "+f"(d[17]), "+f"(d[18]), "+f"(d[19]), "+f"(d[20]), "+f"(d[21]), "+f"(d[22]), "+f"(d[23]), "+f"(d[24]), "+f"(d[25]), "+f"(d[26]), "+f"(d[27]), "+f"(d[28]), "+f"(d[29]), "+f"(d[30]), "+f"(d[31]), "+f"(d[32]), "+f"(d[33]), "+f"(d[34]), "+f"(d[35]), "+f"(d[36]), "+f"(d[37]), "+f"(d[38]), "+f"(d[39]), "+f"(d[40]), "+f"(d[41]), "+f"(d[42]), "+f"(d[43]), "+f"(d[44]), "+f"(d[45]), "+f"(d[46]), "+f"(d[47]), "+f"(d[48]), "+f"(d[49]), "+f"(d[50]), "+f"(d[51]), "+f"(d[52]), "+f"(d[53]), "+f"(d[54]), "+f"(d[55]), "+f"(d[56]), "+f"(d[57]), "+f"(d[58]), "+f"(d[59])
    : "r"(a0), "r"(a1), "r"(a2), "r"(a3), "r"(boff), "n"((uint32_t)BD), "n"((uint32_t)(BD >> 32)));
}
template<int SD, uint64_t BD, int SZ> __device__ __forceinline__ void wg_rs64(float (&d)[SZ], uint32_t a0, uint32_t a1, uint32_t a2, uint32_t a3) {
  if constexpr (SD == 0)
  asm volatile("{\n.reg .pred p;\n.reg .b64 ad, bd;\n.reg .b32 lo;\nsetp.ne.b32 p, 0, 0;\n"
    "mov.b64 bd, %36;\n"
    "wgmma.mma_async.sync.aligned.m64n64k16.f32.bf16.bf16 "
    "{%0, %1, %2, %3, %4, %5, %6, %7, %8, %9, %10, %11, %12, %13, %14, %15, %16, %17, %18, %19, %20, %21, %22, %23, %24, %25, %26, %27, %28, %29, %30, %31}, "
    "{%32, %33, %34, %35}, bd, p, 1, 1, 1;\n}\n"
    : "=f"(d[0]), "=f"(d[1]), "=f"(d[2]), "=f"(d[3]), "=f"(d[4]), "=f"(d[5]), "=f"(d[6]), "=f"(d[7]), "=f"(d[8]), "=f"(d[9]), "=f"(d[10]), "=f"(d[11]), "=f"(d[12]), "=f"(d[13]), "=f"(d[14]), "=f"(d[15]), "=f"(d[16]), "=f"(d[17]), "=f"(d[18]), "=f"(d[19]), "=f"(d[20]), "=f"(d[21]), "=f"(d[22]), "=f"(d[23]), "=f"(d[24]), "=f"(d[25]), "=f"(d[26]), "=f"(d[27]), "=f"(d[28]), "=f"(d[29]), "=f"(d[30]), "=f"(d[31])
    : "r"(a0), "r"(a1), "r"(a2), "r"(a3), "n"(BD));
  if constexpr (SD == 1)
  asm volatile("{\n.reg .pred p;\n.reg .b64 ad, bd;\n.reg .b32 lo;\nsetp.ne.b32 p, 1, 0;\n"
    "mov.b64 bd, %36;\n"
    "wgmma.mma_async.sync.aligned.m64n64k16.f32.bf16.bf16 "
    "{%0, %1, %2, %3, %4, %5, %6, %7, %8, %9, %10, %11, %12, %13, %14, %15, %16, %17, %18, %19, %20, %21, %22, %23, %24, %25, %26, %27, %28, %29, %30, %31}, "
    "{%32, %33, %34, %35}, bd, p, 1, 1, 1;\n}\n"
    : "+f"(d[0]), "+f"(d[1]), "+f"(d[2]), "+f"(d[3]), "+f"(d[4]), "+f"(d[5]), "+f"(d[6]), "+f"(d[7]), "+f"(d[8]), "+f"(d[9]), "+f"(d[10]), "+f"(d[11]), "+f"(d[12]), "+f"(d[13]), "+f"(d[14]), "+f"(d[15]), "+f"(d[16]), "+f"(d[17]), "+f"(d[18]), "+f"(d[19]), "+f"(d[20]), "+f"(d[21]), "+f"(d[22]), "+f"(d[23]), "+f"(d[24]), "+f"(d[25]), "+f"(d[26]), "+f"(d[27]), "+f"(d[28]), "+f"(d[29]), "+f"(d[30]), "+f"(d[31])
    : "r"(a0), "r"(a1), "r"(a2), "r"(a3), "n"(BD));
}
template<int SD, uint64_t BD, int SZ> __device__ __forceinline__ void wg_rs64h(float (&d)[SZ], uint32_t a0, uint32_t a1, uint32_t a2, uint32_t a3) {
  if constexpr (SD == 0)
  asm volatile("{\n.reg .pred p;\n.reg .b64 ad, bd;\n.reg .b32 lo;\nsetp.ne.b32 p, 0, 0;\n"
    "mov.b64 bd, %36;\n"
    "wgmma.mma_async.sync.aligned.m64n64k16.f32.bf16.bf16 "
    "{%0, %1, %2, %3, %4, %5, %6, %7, %8, %9, %10, %11, %12, %13, %14, %15, %16, %17, %18, %19, %20, %21, %22, %23, %24, %25, %26, %27, %28, %29, %30, %31}, "
    "{%32, %33, %34, %35}, bd, p, 1, 1, 1;\n}\n"
    : "=f"(d[32]), "=f"(d[33]), "=f"(d[34]), "=f"(d[35]), "=f"(d[36]), "=f"(d[37]), "=f"(d[38]), "=f"(d[39]), "=f"(d[40]), "=f"(d[41]), "=f"(d[42]), "=f"(d[43]), "=f"(d[44]), "=f"(d[45]), "=f"(d[46]), "=f"(d[47]), "=f"(d[48]), "=f"(d[49]), "=f"(d[50]), "=f"(d[51]), "=f"(d[52]), "=f"(d[53]), "=f"(d[54]), "=f"(d[55]), "=f"(d[56]), "=f"(d[57]), "=f"(d[58]), "=f"(d[59]), "=f"(d[60]), "=f"(d[61]), "=f"(d[62]), "=f"(d[63])
    : "r"(a0), "r"(a1), "r"(a2), "r"(a3), "n"(BD));
  if constexpr (SD == 1)
  asm volatile("{\n.reg .pred p;\n.reg .b64 ad, bd;\n.reg .b32 lo;\nsetp.ne.b32 p, 1, 0;\n"
    "mov.b64 bd, %36;\n"
    "wgmma.mma_async.sync.aligned.m64n64k16.f32.bf16.bf16 "
    "{%0, %1, %2, %3, %4, %5, %6, %7, %8, %9, %10, %11, %12, %13, %14, %15, %16, %17, %18, %19, %20, %21, %22, %23, %24, %25, %26, %27, %28, %29, %30, %31}, "
    "{%32, %33, %34, %35}, bd, p, 1, 1, 1;\n}\n"
    : "+f"(d[32]), "+f"(d[33]), "+f"(d[34]), "+f"(d[35]), "+f"(d[36]), "+f"(d[37]), "+f"(d[38]), "+f"(d[39]), "+f"(d[40]), "+f"(d[41]), "+f"(d[42]), "+f"(d[43]), "+f"(d[44]), "+f"(d[45]), "+f"(d[46]), "+f"(d[47]), "+f"(d[48]), "+f"(d[49]), "+f"(d[50]), "+f"(d[51]), "+f"(d[52]), "+f"(d[53]), "+f"(d[54]), "+f"(d[55]), "+f"(d[56]), "+f"(d[57]), "+f"(d[58]), "+f"(d[59]), "+f"(d[60]), "+f"(d[61]), "+f"(d[62]), "+f"(d[63])
    : "r"(a0), "r"(a1), "r"(a2), "r"(a3), "n"(BD));
}
template<int SD, uint64_t AD, uint64_t BD, int SZ> __device__ __forceinline__ void wg_ss64(float (&d)[SZ], uint32_t aoff) {
  if constexpr (SD == 0)
  asm volatile("{\n.reg .pred p;\n.reg .b64 ad, bd;\n.reg .b32 lo;\nsetp.ne.b32 p, 0, 0;\n"
    "add.u32 lo, %32, %33;\nmov.b64 ad, {lo, %34};\n"
    "mov.b64 bd, %35;\n"
    "wgmma.mma_async.sync.aligned.m64n64k16.f32.bf16.bf16 "
    "{%0, %1, %2, %3, %4, %5, %6, %7, %8, %9, %10, %11, %12, %13, %14, %15, %16, %17, %18, %19, %20, %21, %22, %23, %24, %25, %26, %27, %28, %29, %30, %31}, "
    "ad, bd, p, 1, 1, 0, 1;\n}\n"
    : "=f"(d[0]), "=f"(d[1]), "=f"(d[2]), "=f"(d[3]), "=f"(d[4]), "=f"(d[5]), "=f"(d[6]), "=f"(d[7]), "=f"(d[8]), "=f"(d[9]), "=f"(d[10]), "=f"(d[11]), "=f"(d[12]), "=f"(d[13]), "=f"(d[14]), "=f"(d[15]), "=f"(d[16]), "=f"(d[17]), "=f"(d[18]), "=f"(d[19]), "=f"(d[20]), "=f"(d[21]), "=f"(d[22]), "=f"(d[23]), "=f"(d[24]), "=f"(d[25]), "=f"(d[26]), "=f"(d[27]), "=f"(d[28]), "=f"(d[29]), "=f"(d[30]), "=f"(d[31])
    : "r"(aoff), "n"((uint32_t)AD), "n"((uint32_t)(AD >> 32)), "n"(BD));
  if constexpr (SD == 1)
  asm volatile("{\n.reg .pred p;\n.reg .b64 ad, bd;\n.reg .b32 lo;\nsetp.ne.b32 p, 1, 0;\n"
    "add.u32 lo, %32, %33;\nmov.b64 ad, {lo, %34};\n"
    "mov.b64 bd, %35;\n"
    "wgmma.mma_async.sync.aligned.m64n64k16.f32.bf16.bf16 "
    "{%0, %1, %2, %3, %4, %5, %6, %7, %8, %9, %10, %11, %12, %13, %14, %15, %16, %17, %18, %19, %20, %21, %22, %23, %24, %25, %26, %27, %28, %29, %30, %31}, "
    "ad, bd, p, 1, 1, 0, 1;\n}\n"
    : "+f"(d[0]), "+f"(d[1]), "+f"(d[2]), "+f"(d[3]), "+f"(d[4]), "+f"(d[5]), "+f"(d[6]), "+f"(d[7]), "+f"(d[8]), "+f"(d[9]), "+f"(d[10]), "+f"(d[11]), "+f"(d[12]), "+f"(d[13]), "+f"(d[14]), "+f"(d[15]), "+f"(d[16]), "+f"(d[17]), "+f"(d[18]), "+f"(d[19]), "+f"(d[20]), "+f"(d[21]), "+f"(d[22]), "+f"(d[23]), "+f"(d[24]), "+f"(d[25]), "+f"(d[26]), "+f"(d[27]), "+f"(d[28]), "+f"(d[29]), "+f"(d[30]), "+f"(d[31])
    : "r"(aoff), "n"((uint32_t)AD), "n"((uint32_t)(AD >> 32)), "n"(BD));
}
template<int SD, uint64_t AD, uint64_t BD, int SZ> __device__ __forceinline__ void wg_ss64h(float (&d)[SZ], uint32_t aoff) {
  if constexpr (SD == 0)
  asm volatile("{\n.reg .pred p;\n.reg .b64 ad, bd;\n.reg .b32 lo;\nsetp.ne.b32 p, 0, 0;\n"
    "add.u32 lo, %32, %33;\nmov.b64 ad, {lo, %34};\n"
    "mov.b64 bd, %35;\n"
    "wgmma.mma_async.sync.aligned.m64n64k16.f32.bf16.bf16 "
    "{%0, %1, %2, %3, %4, %5, %6, %7, %8, %9, %10, %11, %12, %13, %14, %15, %16, %17, %18, %19, %20, %21, %22, %23, %24, %25, %26, %27, %28, %29, %30, %31}, "
    "ad, bd, p, 1, 1, 0, 1;\n}\n"
    : "=f"(d[32]), "=f"(d[33]), "=f"(d[34]), "=f"(d[35]), "=f"(d[36]), "=f"(d[37]), "=f"(d[38]), "=f"(d[39]), "=f"(d[40]), "=f"(d[41]), "=f"(d[42]), "=f"(d[43]), "=f"(d[44]), "=f"(d[45]), "=f"(d[46]), "=f"(d[47]), "=f"(d[48]), "=f"(d[49]), "=f"(d[50]), "=f"(d[51]), "=f"(d[52]), "=f"(d[53]), "=f"(d[54]), "=f"(d[55]), "=f"(d[56]), "=f"(d[57]), "=f"(d[58]), "=f"(d[59]), "=f"(d[60]), "=f"(d[61]), "=f"(d[62]), "=f"(d[63])
    : "r"(aoff), "n"((uint32_t)AD), "n"((uint32_t)(AD >> 32)), "n"(BD));
  if constexpr (SD == 1)
  asm volatile("{\n.reg .pred p;\n.reg .b64 ad, bd;\n.reg .b32 lo;\nsetp.ne.b32 p, 1, 0;\n"
    "add.u32 lo, %32, %33;\nmov.b64 ad, {lo, %34};\n"
    "mov.b64 bd, %35;\n"
    "wgmma.mma_async.sync.aligned.m64n64k16.f32.bf16.bf16 "
    "{%0, %1, %2, %3, %4, %5, %6, %7, %8, %9, %10, %11, %12, %13, %14, %15, %16, %17, %18, %19, %20, %21, %22, %23, %24, %25, %26, %27, %28, %29, %30, %31}, "
    "ad, bd, p, 1, 1, 0, 1;\n}\n"
    : "+f"(d[32]), "+f"(d[33]), "+f"(d[34]), "+f"(d[35]), "+f"(d[36]), "+f"(d[37]), "+f"(d[38]), "+f"(d[39]), "+f"(d[40]), "+f"(d[41]), "+f"(d[42]), "+f"(d[43]), "+f"(d[44]), "+f"(d[45]), "+f"(d[46]), "+f"(d[47]), "+f"(d[48]), "+f"(d[49]), "+f"(d[50]), "+f"(d[51]), "+f"(d[52]), "+f"(d[53]), "+f"(d[54]), "+f"(d[55]), "+f"(d[56]), "+f"(d[57]), "+f"(d[58]), "+f"(d[59]), "+f"(d[60]), "+f"(d[61]), "+f"(d[62]), "+f"(d[63])
    : "r"(aoff), "n"((uint32_t)AD), "n"((uint32_t)(AD >> 32)), "n"(BD));
}

constexpr uint64_t dB128 = make_desc(SB, 8192, 1024, 1);
constexpr uint64_t dB128h = make_desc(SB, 4096, 1024, 1);
constexpr uint64_t dB64 = make_desc(SB, 4096, 512, 2);
constexpr uint64_t dA = make_desc(SB + OFF_X, 16, 1024, 1);
template<int I> struct IC { static constexpr int value = I; };
template<int B, int E, class F> __device__ __forceinline__ void sfor(F&& f) { if constexpr (B < E) { f(IC<B>{}); sfor<B + 1, E>(f); } }
#define SFOR(VAR, B, E) sfor<B, E>([&](auto VAR##_) __attribute__((always_inline)) { constexpr int VAR = decltype(VAR##_)::value;
#define SEND });

struct RowC { float c0, c1, c2; };

template<int LO, int HI, int NP, int HOFF>
__device__ __forceinline__ void geglu_slice(uint32_t (&hp)[56], float (&acc)[64], const RowC& a, const RowC& b) {
  #pragma unroll
  for (int i = LO; i < HI; i++) {
    const RowC& c = (i & 1) ? b : a;
    hp[HOFF + i] = pack2(geglu1(acc[2 * i], acc[2 * NP + 2 * i], c.c0, c.c1, c.c2), geglu1(acc[2 * i + 1], acc[2 * NP + 2 * i + 1], c.c0, c.c1, c.c2));
  }
}
__device__ __forceinline__ uint32_t mapa(uint32_t addr, uint32_t rank) { uint32_t r; asm("mapa.shared::cluster.u32 %0, %1, %2;" : "=r"(r) : "r"(addr), "r"(rank)); return r; }
__device__ __forceinline__ void peer_send(float (&acc)[64], uint32_t rbuf, uint32_t rbar) {
  #pragma unroll
  for (int jp = 0; jp < 4; jp++) {
    const int b = 32 + 8 * jp;
    asm volatile("st.async.weak.shared::cluster.mbarrier::complete_tx::bytes.v4.b32 [%0], {%1, %2, %3, %4}, [%5];"
      :: "r"(rbuf + jp * 512), "r"(pack2(acc[b], acc[b + 1])), "r"(pack2(acc[b + 2], acc[b + 3])), "r"(pack2(acc[b + 4], acc[b + 5])), "r"(pack2(acc[b + 6], acc[b + 7])), "r"(rbar) : "memory");
  }
}
template<bool ADD, bool LAST = false>
__device__ __forceinline__ void stage_out(float (&acc)[64], uint32_t lbuf, uint32_t stsm_base, uint32_t lhi, uint32_t l7, uint32_t bar) {
  uint32_t u[16];
  if constexpr (ADD) {
    #pragma unroll
    for (int jp = 0; jp < 4; jp++)
      asm volatile("ld.shared.v4.b32 {%0, %1, %2, %3}, [%4];" : "=r"(u[4 * jp]), "=r"(u[4 * jp + 1]), "=r"(u[4 * jp + 2]), "=r"(u[4 * jp + 3]) : "r"(lbuf + jp * 512) : "memory");
  }
  if constexpr (LAST) { wg_wait<0>(); fence_regs<0, 32>(acc); }
  #pragma unroll
  for (int i = 0; i < 16; i++) { const uint32_t v = pack2(acc[2 * i], acc[2 * i + 1]); u[i] = ADD ? hadd2(v, u[i]) : v; }
  __syncwarp();
  #pragma unroll
  for (int jj = 0; jj < 4; jj++) stsm4(stsm_base + (((2 * jj + lhi) ^ l7) << 4), u[4 * jj], u[4 * jj + 1], u[4 * jj + 2], u[4 * jj + 3]);
  warp_arrive(bar);
}
__device__ __forceinline__ void poll_cnt(const unsigned* cnt, unsigned base, unsigned n) {
  asm volatile("{\n.reg .pred p;\n.reg .u32 c, v;\nmov.u32 c, 0;\nKV_LOOP:\n"
    "ld.relaxed.gpu.global.u32 v, [%0];\nsub.u32 v, v, %1;\nsetp.ge.u32 p, v, %2;\n@p bra KV_DONE;\n"
    "nanosleep.u32 40;\nadd.u32 c, c, 1;\nsetp.lt.u32 p, c, 2000000;\n@p bra KV_LOOP;\ntrap;\nKV_DONE:\n}\n" :: "l"(cnt), "r"(base), "r"(n) : "memory");
}

__global__ void __cluster_dims__(2, 1, 1) __launch_bounds__(384, 1)
fused_kernel(const __grid_constant__ Maps maps, const __nv_bfloat16* __restrict__ x, __nv_bfloat16* __restrict__ out) {
  extern __shared__ __align__(1024) char smraw[];
  const uint32_t sb = smem_u32(smraw);
  const int tid = threadIdx.x;
  const int mt = blockIdx.x >> 3, s = blockIdx.x & 7;
  STAMP(0);
  const uint32_t rank = s & 1;
  uint32_t budget = 0;
  const int w12 = __shfl_sync(0xffffffffu, tid >> 5, 0), wg = w12 >> 2;
  const int qc = 56 * s - 8 * (int)rank;
  if (wg == 2) {
    asm volatile("setmaxnreg.dec.sync.aligned.u32 40;");
    const int warp = w12 - 8;
    STAMPW(40 + warp);
    if (warp != 0 && elect_one()) {
      if (warp == 1) {
        mbar_init(sb + BAR_XW, 8); mbar_init(sb + BAR_XR, 1); mbar_init(sb + BAR_TW, 8); mbar_init(sb + BAR_TILES, 1);
        mbar_init(sb + BAR_KVP, 256); mbar_init(sb + BAR_KVB, 3); mbar_init(sb + BAR_PAR, 1); mbar_init(sb + BAR_RDY2, 2);
        #pragma unroll
        for (int i = 0; i < 8; i++) { mbar_init(sb + BAR_RDY + 8 * i, 1); mbar_init(sb + BAR_OW + 8 * i, 4); }
      } else {
        #pragma unroll
        for (int i = 0; i < 16; i++) mbar_init(sb + BAR_DAT + 8 * ((warp - 2) * 16 + i), 1);
      }
      asm volatile("fence.mbarrier_init.release.cluster;" ::: "memory");
    }
    __syncwarp();
    STAMPW(44 + warp);
    asm volatile("barrier.cluster.arrive.relaxed.aligned;" ::: "memory");
    asm volatile("bar.sync 5, 384;" ::: "memory");
    if (warp == 0) {
      STAMPW(48);
      {
        const int lane = lane_id(), t = lane + 34;
        mbar_expect_tx(sb + BAR_DAT + 8 * lane, 2048);
        mbar_expect_tx(sb + BAR_FULL + 8 * (lane + 2), lane >= 19 && lane < 26 ? 16384 - 1024 * rank : 16384);
        if (t < 39) mbar_expect_tx(sb + BAR_FULL + 8 * t, t == 34 ? 16384 : (t == 35 ? 57344 : (t == 36 ? 53248 : 73728)));
        __syncwarp();
      }
      const uint32_t el = elect_one();
      #define FREED(T) asm volatile("bar.sync %0, 96;" :: "r"(8 + ((T) & 7)) : "memory")
      const int ck = 64 * rank, cs = 64 * (rank ^ 1);
      const int f32 = 224 * s + 192 * (rank ^ 1), f64 = 224 * s + 32 * rank;
      if (el) {
        #pragma unroll 1
        for (int i = 2; i < 12; i++) prefetch_map(&maps.x + i);
        mbar_wait(sb + BAR_X + 8 * XWAIT);
        #pragma unroll 1
        for (int t = 2; t < 7; t++) {
          const uint32_t fb = sb + BAR_FULL + 8 * t, dst = sb + OFF_SLOT + (t ^ ((t >> 1) == 2)) * 16384;
          STAMPW(64 + t);
          tma2d(dst, &maps.qkv, fb, 448 + qc, t * 64);
          tma2d(dst + 8192, &maps.qkv, fb, 896 + qc, t * 64);
        }
      }
      __syncwarp();
      {
        uint32_t dst = sb + OFF_SLOT, fb = sb + BAR_FULL + 8 * 7;
        int col = f64, kr = 0, dp = 0;
        #pragma unroll 1
        for (int t = 7; t < 35; t++) {
          if (t != 16) { FREED(dp); dp += t == 11 ? 3 : 1; }
          STAMPW(64 + t);
          if (elect_one()) {
            if (t >= 21 && t < 28) {
              tma2d(dst, &maps.g32, fb, f32, kr);
              tma2d(dst + 4096, &maps.u32, fb, f32, kr);
              tma2d(dst + 8192, &maps.q32, fb, 56 * s + 24 * rank, kr);
              tma2d(dst + 12288, &maps.q32 + rank, fb, 56 * s + 32 * (rank ^ 1), kr);
            } else {
              tma2d(dst, &maps.g, fb, col, kr);
              tma2d(dst + 8192, &maps.u, fb, col, kr);
            }
          }
          dst += t == 10 ? 32768 : 16384; fb += 8;
          if (dst == sb + OFF_SLOT + 6 * 16384) dst = sb + OFF_SLOT;
          kr += 64;
          if (kr == 448) { kr = 0; if (t != 27) col += 64; }
        }
      }
      #pragma unroll
      for (int i = 0; i < 18; i++) {
        const int t = ord_of(i);
        if (dep_of(i)) FREED(dep_of(i));
        const uint32_t fb = sb + BAR_FULL + 8 * (t < 39 ? 35 : (t < 43 ? 36 : (t < 48 ? 37 : 38))), dst = sb + buf_off(t);
        STAMPW(64 + t);
        const bool dir = t >= 40 && t < 43;
        const int v = t < 40 ? t - 35 : t - 38, p = v >= 10 ? 2 : (v >= 5), st = dir ? 2 * (t - 40) : v - 5 * p;
        const int sb2 = dir ? st + 1 : st;
        const int r0 = st == 0 ? 56 * s : (st == 1 ? f32 : f64 + 64 * (st - 2)), r1 = sb2 == 0 ? 56 * s : (sb2 == 1 ? f32 : f64 + 64 * (sb2 - 2));
        if (elect_one()) {
          tma2d(dst, &maps.o - (st < 2 ? st : 2), fb, dir ? 384 : 128 * p + ck, r0);
          if (t != 42) tma2d(dst + (st == 1 ? 4096 : 8192), &maps.o - (sb2 < 2 ? sb2 : 2), fb, dir ? 384 : 128 * p + cs, r1);
        }
      }
      STAMPW(1);
    } else {
      unsigned* cnt = &g_cnt[s * 32];
      unsigned* cnt2 = &g_cnt2[mt * 32];
      const int lane = lane_id();
      unsigned e = 0;
      if (lane == 0) { asm volatile("ld.relaxed.gpu.global.u32 %0, [%1];" : "=r"(e) : "l"(cnt) : "memory"); e >>= 4; }
      e = __shfl_sync(0xffffffffu, e, 0);
      const unsigned par = e & 1;
      asm volatile("barrier.cluster.wait.acquire.aligned;" ::: "memory");
      if (warp == 2) {
        mbar_wait(sb + BAR_FULL + 8 * 5);
        const uint4* src = (const uint4*)(x + (mt * 128 + s * 16) * DM) + lane;
        uint4* dst = (uint4*)(out + (mt * 128 + s * 16) * DM) + lane;
        #pragma unroll 1
        for (int b = 0; b < 4; b++) {
          uint4 v[7];
          #pragma unroll
          for (int i = 0; i < 7; i++) v[i] = __ldg(src + (b * 7 + i) * 32);
          #pragma unroll
          for (int i = 0; i < 7; i++) dst[(b * 7 + i) * 32] = v[i];
        }
        __syncwarp();
        if (lane == 0) asm volatile("red.release.gpu.global.add.u32 [%0], 1;" :: "l"(cnt2) : "memory");
      } else if (warp == 3) {
        mbar_wait(sb + BAR_XW); fence_async(); if (lane == 0) mbar_arrive(sb + BAR_XR);
        mbar_wait(sb + BAR_TW); fence_async(); if (lane == 0) mbar_arrive(sb + BAR_TILES);
      } else if (mt == 0) {
        float4* z = (float4*)&g_kvsum[((par ^ 1u) * 8 + s) * KVN];
        #pragma unroll 1
        for (int i = 0; i < 21; i++) z[lane + 32 * i] = make_float4(0.f, 0.f, 0.f, 0.f);
      }
      const float* sum = &g_kvsum[(par * 8 + s) * KVN];
      if (warp == 1 && lane == 0) asm volatile("st.shared.u32 [%0], %1;" :: "r"(sb + OFF_PAR), "r"(par) : "memory");
      if (warp == 1) { __syncwarp(); if (lane == 0) mbar_arrive(sb + BAR_PAR); }
      mbar_wait(sb + BAR_KVP);
      if (warp == 1) {
        STAMPW(2);
        if (lane == 0) asm volatile("red.release.gpu.global.add.u32 [%0], 1;" :: "l"(cnt) : "memory");
        STAMPW(3);
      } else {
        #pragma unroll
        for (int i = 0; i < 8; i++)
          asm volatile("st.shared.v4.u32 [%0], {%1, %1, %1, %1};" :: "r"(sb + OFF_KVB + ((warp - 2) * 256 + lane + 32 * i) * 16), "r"(0) : "memory");
      }
      asm volatile("bar.sync 3, 96;" ::: "memory");
      if (lane == 0) poll_cnt(cnt, e << 4, 16);
      __syncwarp();
      if (warp == 1) STAMPW(4);
      float4 v[7];
      #pragma unroll
      for (int n = 0; n < 7; n++) {
        const float* p = sum + (((warp - 1) * 7 + n) * 32 + lane) * 4;
        asm volatile("ld.relaxed.gpu.global.v4.f32 {%0, %1, %2, %3}, [%4];" : "=f"(v[n].x), "=f"(v[n].y), "=f"(v[n].z), "=f"(v[n].w) : "l"(p) : "memory");
      }
      #pragma unroll
      for (int n = 0; n < 7; n++) {
        const int f = (warp - 1) * 7 + n, g = f >> 2, hb = g >= 2;
        int d = (g - hb) * 16 + (lane >> 2), c = 24 * hb + 8 * (f & 3) + 2 * (lane & 3);
        unsigned lo = 28 * hb, lim = (unsigned)(c - lo) < 28u ? 28u : 0u;
        if (n == 6 && warp == 3) { d = (lane >> 3) * 16 + (lane & 7); c = 56; lo = 0; lim = 56; }
        const uint32_t a = sb + OFF_KVB + d * 128 + (((c >> 3) ^ (d & 7)) << 4) + (c & 7) * 2;
        const uint32_t a0 = a + rank * (d >= 24 ? -24 * 128 : 32 * 128), a1 = a + 1024 + rank * (d >= 16 ? -24 * 128 : 32 * 128);
        asm volatile("{\n.reg .pred p, q;\nsetp.lt.u32 p, %4, %6;\nsetp.lt.u32 q, %5, %6;\n@p st.shared.u32 [%0], %2;\n@q st.shared.u32 [%1], %3;\n}"
          :: "r"(a0), "r"(a1), "r"(pack2(v[n].x, v[n].y)), "r"(pack2(v[n].z, v[n].w)), "r"(d - lo), "r"(d + 8 - lo), "r"(lim) : "memory");
      }
      if (warp == 1) STAMPW(9);
      fence_async();
      __syncwarp();
      if (lane == 0) mbar_arrive(sb + BAR_KVB);
      if (warp == 1) STAMPW(5);
      if (warp < 3 && elect_one()) {
        poll_cnt(cnt2, e << 3, 8);
        asm volatile("fence.proxy.async;" ::: "memory");
        if (warp == 2) STAMPW(7);
        #pragma unroll 1
        for (int i = 0; i < 4; i++) {
          mbar_wait(sb + BAR_OW + (warp - 1) * 32 + i * 8);
          fence_async();
          const int p = (i + 3) & 3;
          asm volatile("cp.reduce.async.bulk.tensor.2d.global.shared::cta.add.tile.bulk_group [%0, {%2, %3}], [%1];"
            :: "l"(&maps.out), "r"(sb + OFF_X + (3 + p) * 16384 + (warp - 1) * 8192), "r"(128 * p + (i ? 64 * (int)rank : 0)), "r"(mt * 128 + (warp - 1) * 64) : "memory");
          if (warp == 2) STAMPW(20 + i);
        }
        asm volatile("cp.async.bulk.commit_group;" ::: "memory");
        asm volatile("cp.async.bulk.wait_group.read 0;" ::: "memory");
        if (warp == 2) STAMPW(12);
      }
    }
    __syncwarp();
    return;
  }

  if (elect_one()) {
    if (w12 == 0) {
      #pragma unroll
      for (int i = 0; i < 7; i++) mbar_init(sb + BAR_X + 8 * i, 1);
      fence_async();
      STAMP(14);
      #pragma unroll
      for (int i = 0; i < 7; i++) { mbar_expect_tx(sb + BAR_X + 8 * i, 16384); tma2d(sb + OFF_X + i * 16384, &maps.x, sb + BAR_X + 8 * i, i * 64, mt * 128); }
      mbar_init(sb + BAR_FULL, 1); mbar_init(sb + BAR_FULL + 8, 1);
      fence_async();
      #pragma unroll
      for (int t = 0; t < 2; t++) {
        mbar_expect_tx(sb + BAR_FULL + 8 * t, 16384);
        tma2d(sb + buf_off(t), &maps.qkv, sb + BAR_FULL + 8 * t, 448 + qc, t * 64);
        tma2d(sb + buf_off(t) + 8192, &maps.qkv, sb + BAR_FULL + 8 * t, 896 + qc, t * 64);
      }
      STAMP(15);
    } else {
      if ((sb & 0xFFFFFFu) != SB) __trap();
      #pragma unroll
      for (int i = 0; i < 6; i++) mbar_init(sb + BAR_FULL + 8 * (w12 * 6 - 4 + i), 1);
      mbar_init(sb + BAR_EMPTY + 8 * w12, 2);
      fence_async();
    }
  }
  __syncwarp();
  STAMP(40);
  asm volatile("barrier.cluster.arrive.relaxed.aligned;" ::: "memory");
  asm volatile("bar.sync 5, 384;" ::: "memory");
  STAMP(41);
  asm volatile("setmaxnreg.inc.sync.aligned.u32 232;");
  STAMP(42);
  const int lane = lane_id(), wl = w12 & 3, w8 = w12;
  const int q = lane & 3;
  const uint32_t is0 = (tid & 127) == 0;
  const uint32_t fb = sb + BAR_FULL, eb = sb + BAR_EMPTY;
  const uint32_t aoff = wg * 512;
  const uint32_t lrow = (lane & 7) + ((lane >> 3) & 1) * 8, lhi = lane >> 4, l7 = lane & 7;

  #define REL(T) do { if constexpr ((T) == 5 || (T) == 6) mbar_arrive_pred(eb + 8 * (T), is0); \
    else asm volatile("{\n.reg .pred p;\nsetp.eq.u32 p, %0, 0;\n@p bar.arrive %1, 96;\n}" :: "r"(wl), "n"(8 + ((T) & 7)) : "memory"); } while (0)
  float accA[64], accB[64];
  uint32_t hp[56];
  RowC ca, cb;
  float ra, rb, rla, rlb;
  uint32_t xr[112];
  {
    float s0[4] = {0.f, 0.f, 0.f, 0.f}, s1[4] = {0.f, 0.f, 0.f, 0.f};
    const uint32_t xrow = sb + OFF_X + (w8 * 16 + lrow) * 128;
    #pragma unroll
    for (int kb = 0; kb < 7; kb++) {
      mbar_wait(sb + BAR_X + 8 * kb);
      STAMP(32 + kb);
      #pragma unroll
      for (int kk = 0; kk < 4; kk++) {
        const int i = (kb * 4 + kk) * 4;
        ldsm4(xr[i], xr[i + 1], xr[i + 2], xr[i + 3], xrow + kb * 16384 + (((2 * kk + lhi) ^ l7) << 4));
      }
      #pragma unroll
      for (int kk = 0; kk < 4; kk++) {
        const int i = (kb * 4 + kk) * 4;
        if (kk & 1) mma_rowsum(s1, xr[i], xr[i + 1], xr[i + 2], xr[i + 3]); else mma_rowsum(s0, xr[i], xr[i + 1], xr[i + 2], xr[i + 3]);
      }
    }
    STAMP(1);
    const float meanA = (s0[0] + s1[0]) * (1.0f / DM), meanB = (s0[2] + s1[2]) * (1.0f / DM);
    const uint32_t mA = pack2(meanA, meanA), mB = pack2(meanB, meanB);
    const float dmA = meanA - bf_lo(mA), dmB = meanB - bf_lo(mB);
    #pragma unroll
    for (int i = 0; i < 32; i++) xr[i] = hsub2(xr[i], (i & 1) ? mB : mA);
    #pragma unroll
    for (int kk = 0; kk < 4; kk++) stsm4(xrow + (((2 * kk + lhi) ^ l7) << 4), xr[4 * kk], xr[4 * kk + 1], xr[4 * kk + 2], xr[4 * kk + 3]);
    float vA = 0.f, vB = 0.f;
    SFOR(kb, 0, 7)
      mbar_wait(fb + 8 * kb);
      STAMP(64 + kb);
      wg_fence();
      SFOR(kk, 0, 4)
        constexpr int i = (kb * 4 + kk) * 4;
        wg_rs120<(kb | kk) != 0, dB128 + ((buf_off(kb) + kk * 2048) >> 4)>(accA, xr[i], xr[i + 1], xr[i + 2], xr[i + 3], rank);
      SEND
      wg_commit();
      if constexpr (kb < 5) {
        #pragma unroll
        for (int i = 16 * (kb + 2); i < 16 * (kb + 3); i++) xr[i] = hsub2(xr[i], (i & 1) ? mB : mA);
      }
      if constexpr (kb > 0) { wg_wait<1>(); REL(kb - 1); }
      if constexpr (kb < 6) {
        #pragma unroll
        for (int kk = 0; kk < 4; kk++) {
          const int i = ((kb + 1) * 4 + kk) * 4;
          stsm4(xrow + (kb + 1) * 16384 + (((2 * kk + lhi) ^ l7) << 4), xr[i], xr[i + 1], xr[i + 2], xr[i + 3]);
        }
      }
      if constexpr (kb == 5) warp_arrive(sb + BAR_XW);
      #pragma unroll
      for (int b2 = kb; b2 < (kb == 5 ? 7 : kb + 1) && kb < 6; b2++) {
        uint32_t qa = 0, qb = 0;
        #pragma unroll
        for (int i = 16 * b2; i < 16 * b2 + 16; i += 2) { qa = hfma2(xr[i], xr[i], qa); qb = hfma2(xr[i + 1], xr[i + 1], qb); }
        vA += bf_lo(qa) + bf_hi(qa); vB += bf_lo(qb) + bf_hi(qb);
      }
      if constexpr (kb == 6) {
        mbar_wait(fb + 8 * 7);
        vA += __shfl_xor_sync(0xffffffffu, vA, 1); vB += __shfl_xor_sync(0xffffffffu, vB, 1);
        vA += __shfl_xor_sync(0xffffffffu, vA, 2); vB += __shfl_xor_sync(0xffffffffu, vB, 2);
        vA = fmaxf(fmaf(vA, 1.0f / DM, -dmA * dmA), 0.f); vB = fmaxf(fmaf(vB, 1.0f / DM, -dmB * dmB), 0.f);
        ra = rcp(bf_round(sqrt_approx(bf_round(bf_round(vA) + 1e-5f))));
        rb = rcp(bf_round(sqrt_approx(bf_round(bf_round(vB) + 1e-5f))));
        asm volatile("" : "+f"(ra), "+f"(rb) :: "memory");
      }
    SEND
  }
  STAMP(2);
  #define SS_ISSUE(ACC, T) \
    SFOR(kk, 0, 4) \
      wg_ss128<(kb | kk) != 0, dA + ((kb * 16384 + kk * 32) >> 4), dB128 + ((buf_off(T) + kk * 2048) >> 4)>(ACC, aoff); \
    SEND
  {
    float (&kvacc)[64] = accA;
    const uint32_t trow = sb + OFF_SLOT + (4 + 2 * wg) * 16384 + (wl * 16 + lrow) * 128;
    constexpr uint64_t dKV = dB128 + ((OFF_SLOT + 4 * 16384) >> 4);
    uint32_t pk[14];
    SFOR(kb, 0, 7)
      constexpr int t = 7 + kb;
      mbar_wait(fb + 8 * t);
      if constexpr (kb == NRS) mbar_wait(sb + BAR_XR);
      if constexpr (kb == 3) mbar_wait(sb + BAR_TILES);
      STAMP(64 + t);
      wg_fence();
      if constexpr (kb < NRS) {
        SFOR(kk, 0, 4)
          constexpr int i = (kb * 4 + kk) * 4;
          wg_rs128<(kb | kk) != 0, dB128 + ((buf_off(t) + kk * 2048) >> 4)>(accB, xr[i], xr[i + 1], xr[i + 2], xr[i + 3]);
        SEND
      } else {
        SS_ISSUE(accB, t)
      }
      if constexpr (kb == 3) {
        SFOR(kk, 0, 8)
          constexpr uint64_t da = dKV + (kk >> 2) * 2048 + (kk & 3) * 128;
          wg_ss40t<kk != 0, da, da + 512>(kvacc, wg * 3);
        SEND
      }
      wg_commit();
      if constexpr (kb == 0) {
        ca.c0 = 0.7978845608f * ra; ca.c1 = 0.0356774081f * ra * ra * ra; ca.c2 = 0.5f * ra * ra;
        cb.c0 = 0.7978845608f * rb; cb.c1 = 0.0356774081f * rb * rb * rb; cb.c2 = 0.5f * rb * rb;
        rla = ra * 1.4426950409f; rlb = rb * 1.4426950409f;
      }
      wg_wait<1>();
      if constexpr (kb == 0) fence_regs<0, 60>(accA);
      REL(t - 1);
      if constexpr (kb == 0) {
        #pragma unroll
        for (int i = 0; i < 8; i++) pk[i] = (i & 1) ? phi2(accA[2 * i], accA[2 * i + 1], rb, rlb) : phi2(accA[2 * i], accA[2 * i + 1], ra, rla);
      } else if constexpr (kb == 1) {
        mbar_wait(eb + 8 * (5 + wg));
        fence_regs<16, 60>(accA);
        #pragma unroll
        for (int jj = 0; jj < 2; jj++) stsm4(trow + (((2 * jj + lhi) ^ l7) << 4), pk[4 * jj], pk[4 * jj + 1], pk[4 * jj + 2], pk[4 * jj + 3]);
        uint32_t vv[14];
        #pragma unroll
        for (int i = 0; i < 14; i++) { const float r = (i & 1) ? rb : ra; vv[i] = pack2(accA[32 + 2 * i] * r, accA[33 + 2 * i] * r); }
        #pragma unroll
        for (int jj = 0; jj < 3; jj++) stsm4(trow + 8192 + (((2 * jj + lhi) ^ l7) << 4), vv[4 * jj], vv[4 * jj + 1], vv[4 * jj + 2], vv[4 * jj + 3]);
        const uint32_t one = q == 0 ? 0x00003F80u : 0u;
        stsm4(trow + 8192 + (((6 + lhi) ^ l7) << 4), vv[12], vv[13], one, one);
        #pragma unroll
        for (int i = 8; i < 14; i++) pk[i] = (i & 1) ? phi2(accA[2 * i], accA[2 * i + 1], rb, rlb) : phi2(accA[2 * i], accA[2 * i + 1], ra, rla);
        stsm4(trow + (((4 + lhi) ^ l7) << 4), pk[8], pk[9], pk[10], pk[11]);
        stsm4(trow + (((6 + lhi) ^ l7) << 4), pk[12], pk[13], 0u, 0u);
        warp_arrive(sb + BAR_TW);
      } else if constexpr (kb == 4) {
        fence_regs<0, 20>(kvacc);
        mbar_wait(sb + BAR_PAR);
        uint32_t par;
        asm volatile("ld.shared.u32 %0, [%1];" : "=r"(par) : "r"(sb + OFF_PAR) : "memory");
        float* sum = &g_kvsum[(par * 8 + s) * KVN];
        const uint32_t okw = wg == 0 ? (wl < 2) : (wl >= 1);
        const bool hb0 = wl >= 2, hb1 = wl * 16 + (lane >> 2) >= 20;
        float* p = sum + ((wg == 0 ? wl * 4 : 4 + wl * 4) * 32 + lane) * 4;
        #pragma unroll
        for (int j = 0; j < 4; j++)
          asm volatile("{\n.reg .pred p;\nsetp.ne.u32 p, %5, 0;\n@p red.relaxed.gpu.global.add.v4.f32 [%0], {%1, %2, %3, %4};\n}"
            :: "l"(p + j * 128), "f"(kvacc[4 * j]), "f"(kvacc[4 * j + 1]), "f"(kvacc[4 * j + 2]), "f"(kvacc[4 * j + 3]), "r"(okw) : "memory");
        asm volatile("{\n.reg .pred p;\nsetp.ne.u32 p, %5, 0;\n@p red.relaxed.gpu.global.add.v4.f32 [%0], {%1, %2, %3, %4};\n}"
          :: "l"(sum + (20 * 32 + wl * 8 + (lane >> 2)) * 4), "f"(hb0 ? 0.f : kvacc[16]), "f"(hb0 ? kvacc[16] : 0.f), "f"(hb1 ? 0.f : kvacc[18]), "f"(hb1 ? kvacc[18] : 0.f), "r"((uint32_t)(wg == 1 && q == 0)) : "memory");
        mbar_arrive(sb + BAR_KVP);
      }
    SEND
  }
  STAMP(3);
  #define EPI16(ACC, HOFF) \
    if constexpr (kb == 0) geglu_slice<0, 3, 16, HOFF>(hp, ACC, ca, cb); \
    else if constexpr (kb >= 2 && kb < 5) geglu_slice<3 * kb - 3, 3 * kb, 16, HOFF>(hp, ACC, ca, cb); \
    else if constexpr (kb >= 5) geglu_slice<2 * kb + 2, 2 * kb + 4, 16, HOFF>(hp, ACC, ca, cb);
  SFOR(kb, 0, 7)
    constexpr int t = 14 + kb;
    mbar_wait(fb + 8 * t);
    STAMP(64 + t);
    wg_fence();
    SS_ISSUE(accA, t)
    wg_commit();
    wg_wait<1>();
    if constexpr (kb == 0) fence_regs<0, 64>(accB);
    REL(t - 1);
    EPI16(accB, 8)
  SEND
  STAMP(4);
  SFOR(kb, 0, 7)
    constexpr int t = 21 + kb;
    mbar_wait(fb + 8 * t);
    STAMP(64 + t);
    wg_fence();
    SFOR(kk, 0, 4)
      wg_ss120<(kb | kk) != 0, dA + ((kb * 16384 + kk * 32) >> 4), dB64 + ((buf_off(t) + kk * 1024) >> 4)>(accB, aoff);
    SEND
    wg_commit();
    wg_wait<1>();
    if constexpr (kb == 0) fence_regs<0, 64>(accA);
    REL(t - 1);
    EPI16(accA, 24)
  SEND
  STAMP(5);
  uint32_t op[14];
  {
    uint32_t pq[14];
    SFOR(kb, 0, 7)
      constexpr int t = 28 + kb;
      mbar_wait(fb + 8 * t);
      if constexpr (kb == 4) mbar_wait(sb + BAR_KVB);
      if constexpr (kb == 6) asm volatile("{\n.reg .pred p;\nsetp.eq.u32 p, %0, 0;\n@p bar.sync 6, 256;\n}" :: "r"(wg) : "memory");
      STAMP(64 + t);
      wg_fence();
      SS_ISSUE(accA, t)
      if constexpr (kb == 4) {
        SFOR(kk, 0, 3)
          wg_rs64h<kk != 0, dB128 + ((OFF_KVB + kk * 2048) >> 4)>(accB, pq[4 * kk], pq[4 * kk + 1], pq[4 * kk + 2], pq[4 * kk + 3]);
        SEND
        wg_rs64h<1, dB128 + ((OFF_KVB + 6144) >> 4)>(accB, pq[12], pq[13], 0u, 0u);
      }
      wg_commit();
      if constexpr (kb == 6) asm volatile("{\n.reg .pred p;\nsetp.ne.u32 p, %0, 0;\n@p bar.arrive 6, 256;\n}" :: "r"(wg) : "memory");
      wg_wait<1>();
      if constexpr (kb == 0) fence_regs<0, 60>(accB);
      REL(t - 1);
      constexpr int plo = kb == 0 ? 0 : 5 * kb - 5, phi_ = kb == 0 ? 5 : (kb == 1 ? 0 : 5 * kb);
      #pragma unroll
      for (int i = plo; i < phi_ && i < 14; i++)
        pq[i] = (i & 1) ? phi2(accB[32 + 2 * i], accB[33 + 2 * i], rb, rlb) : phi2(accB[32 + 2 * i], accB[33 + 2 * i], ra, rla);
      if constexpr (kb >= 3 && kb < 6) geglu_slice<kb == 3 ? 0 : 4 * kb - 15, kb == 5 ? 8 : 4 * kb - 11, 8, 0>(hp, accB, ca, cb);
      if constexpr (kb == 5) {
        fence_regs<32, 64>(accB);
        float dn[4];
        #pragma unroll
        for (int i = 0; i < 4; i++) dn[i] = rcp(__shfl_sync(0xffffffffu, accB[60 + i], lane & ~3) + 1e-6f);
        #pragma unroll
        for (int i = 0; i < 14; i++) {
          const int j = i >> 1, hf = i & 1;
          const float dv = j < 3 ? dn[2 * hf] : (j > 3 ? dn[2 * hf + 1] : (q < 2 ? dn[2 * hf] : dn[2 * hf + 1]));
          op[i] = pack2(accB[32 + 2 * i] * dv, accB[33 + 2 * i] * dv);
        }
      }
    SEND
  }
  STAMP(6);
  const uint32_t xb = sb + OFF_X + 3 * 16384 + w8 * 2048;
  const uint32_t peer_xb = mapa(xb + lane * 16, rank ^ 1), peer_bar = mapa(sb + BAR_DAT + w8 * 32, rank ^ 1);
  const uint32_t owb = sb + BAR_OW + wg * 32;
  #define PP_WAIT() asm volatile("bar.sync %0, 256;" :: "r"(6 + wg) : "memory")
  #define PP_PASS() asm volatile("bar.arrive %0, 256;" :: "r"(7 - wg) : "memory")
  #define FULL(T) mbar_wait(fb + 8 * (T))
  #define G2_AB(WG, ACC, T, O, OH) \
    WG<0, (dB128 + ((buf_off(T) + (O)) >> 4))>(ACC, op[0], op[1], op[2], op[3]); \
    WG<1, (dB128 + ((buf_off(T) + (O) + 2048) >> 4))>(ACC, op[4], op[5], op[6], op[7]); \
    WG<1, (dB128 + ((buf_off(T) + (O) + 4096) >> 4))>(ACC, op[8], op[9], op[10], op[11]); \
    WG<1, (dB128 + ((buf_off(T) + (O) + 6144) >> 4))>(ACC, op[12], op[13], 0u, 0u); \
    WG<1, (dB128h + ((OH) >> 4))>(ACC, hp[0], hp[1], hp[2], hp[3]); \
    WG<1, (dB128h + (((OH) + 2048) >> 4))>(ACC, hp[4], hp[5], hp[6], hp[7]);
  #define G2_H(WG, ACC, OFF, H0, K0, K1) \
    SFOR(kk, K0, K1) \
      WG<1, (dB128 + (((OFF) + kk * 2048) >> 4))>(ACC, hp[(H0) + 4 * kk], hp[(H0) + 4 * kk + 1], hp[(H0) + 4 * kk + 2], hp[(H0) + 4 * kk + 3]); \
    SEND
  #define XSEND(ACC, P) peer_send(ACC, peer_xb + (P) * 16384, peer_bar + (P) * 8)
  #define XRECV(ACC, P) mbar_wait(sb + BAR_DAT + w8 * 32 + (P) * 8); STAMP(26 + (P)); \
    stage_out<true, (P) == 2>(ACC, xb + (P) * 16384 + lane * 16, xb + (P) * 16384 + lrow * 128, lhi, l7, owb + 8 + (P) * 8)
  #define PP_WAIT_IF(W) asm volatile("{\n.reg .pred p;\nsetp.eq.u32 p, %0, " #W ";\n@p bar.sync 6 + " #W ", 256;\n}" :: "r"(wg) : "memory")
  #define PP_PASS_IF(W) asm volatile("{\n.reg .pred p;\nsetp.eq.u32 p, %0, " #W ";\n@p bar.arrive 7 - " #W ", 256;\n}" :: "r"(wg) : "memory")
  #define BURST1(W) \
      FULL(35); \
      if (W == 1) PP_WAIT(); \
      STAMP(64 + 35); \
      wg_fence(); \
      G2_AB(wg_rs128, accB, 35, 0, buf_off(36)) \
      G2_H(wg_rs128, accB, buf_off(37), 8, 0, 4) \
      G2_H(wg_rs128, accB, buf_off(38), 24, 0, 3) \
      wg_commit(); \
      if (W == 0) PP_PASS(); \
      G2_H(wg_rs128, accB, buf_off(38), 24, 3, 4) \
      wg_commit(); \
      if (W == 1) FULL(36); \
      wg_wait<1>(); \
      STAMP(64 + 36); \
      REL(37);
  #define EPI4() \
      fence_regs<0, 64>(accA); \
      REL(34); \
      asm volatile("{\n.reg .pred p;\nelect.sync _|p, 0xffffffff;\n@p mbarrier.arrive.shared::cluster.b64 _, [%0];\n}" :: "r"(mapa(sb + BAR_RDY + w8 * 8, rank ^ 1)) : "memory"); \
      FULL(35); \
      geglu_slice<0, 16, 16, 40>(hp, accA, ca, cb); \
      STAMP(64 + 37);
  if (wg == 0) {
    BURST1(0)
    EPI4()
    FULL(36);
    PP_WAIT();
  } else {
    wg_wait<0>();
    EPI4()
    BURST1(1)
  }
  STAMP(64 + 38);
  wg_fence();
  G2_H(wg_rs128, accB, buf_off(39), 40, 0, 4)
  G2_AB(wg_rs64, accA, 40, 0, buf_off(40) + 8192)
  G2_H(wg_rs64, accA, buf_off(41), 8, 0, 8)
  G2_H(wg_rs64, accA, buf_off(42), 40, 0, 2)
  wg_commit();
  PP_PASS();
  G2_H(wg_rs64, accA, buf_off(42), 40, 2, 4)
  wg_commit();
  wg_wait<1>();
  fence_regs<0, 64>(accB);
  STAMP(64 + 39);
  REL(41);
  asm volatile("{\n.reg .pred p;\nsetp.ne.u32 p, %1, 0;\n@p mbarrier.arrive.shared::cluster.b64 _, [%0];\n}" :: "r"(mapa(sb + BAR_RDY2, rank ^ 1)), "r"(is0) : "memory");
  mbar_wait(sb + BAR_RDY + w8 * 8);
  XSEND(accB, 0);
  wg_wait<0>();
  fence_regs<0, 32>(accA);
  stage_out<false>(accA, 0, xb + 3 * 16384 + lrow * 128, lhi, l7, owb);
  FULL(37);
  STAMP(64 + 40);
  PP_WAIT();
  STAMP(64 + 41);
  wg_fence();
  G2_AB(wg_rs128, accA, 43, 0, buf_off(44))
  G2_H(wg_rs128, accA, buf_off(45), 8, 0, 4)
  G2_H(wg_rs128, accA, buf_off(46), 24, 0, 4)
  G2_H(wg_rs128, accA, buf_off(47), 40, 0, 3)
  wg_commit();
  PP_PASS();
  G2_H(wg_rs128, accA, buf_off(47), 40, 3, 4)
  wg_commit();
  XRECV(accB, 0);
  mbar_wait(sb + BAR_RDY2);
  wg_wait<0>();
  fence_regs<0, 64>(accA);
  STAMP(64 + 42);
  XSEND(accA, 1);
  FULL(38);
  STAMP(64 + 43);
  PP_WAIT();
  STAMP(64 + 44);
  wg_fence();
  G2_AB(wg_rs64h, accB, 48, 8192, buf_off(49) + 4096)
  G2_H(wg_rs64h, accB, buf_off(50) + 8192, 8, 0, 4)
  G2_H(wg_rs64h, accB, buf_off(51) + 8192, 24, 0, 4)
  G2_H(wg_rs64h, accB, buf_off(52) + 8192, 40, 0, 2)
  wg_commit();
  PP_PASS();
  G2_H(wg_rs64h, accB, buf_off(52) + 8192, 40, 2, 4)
  wg_commit();
  XRECV(accA, 1);
  wg_wait<0>();
  fence_regs<32, 64>(accB);
  STAMP(64 + 45);
  XSEND(accB, 2);
  STAMP(64 + 46);
  PP_WAIT();
  STAMP(64 + 47);
  wg_fence();
  G2_AB(wg_rs64, accB, 48, 0, buf_off(49))
  G2_H(wg_rs64, accB, buf_off(50), 8, 0, 4)
  G2_H(wg_rs64, accB, buf_off(51), 24, 0, 4)
  G2_H(wg_rs64, accB, buf_off(52), 40, 0, 2)
  wg_commit();
  PP_PASS_IF(1);
  G2_H(wg_rs64, accB, buf_off(52), 40, 2, 4)
  wg_commit();
  XRECV(accB, 2);
  STAMP(12);
}

typedef CUresult (*PFN_enc)(CUtensorMap*, CUtensorMapDataType, cuuint32_t, void*, const cuuint64_t*, const cuuint64_t*, const cuuint32_t*, const cuuint32_t*,
                            CUtensorMapInterleave, CUtensorMapSwizzle, CUtensorMapL2promotion, CUtensorMapFloatOOBfill);
void enc2d(PFN_enc enc, CUtensorMap* m, const void* base, uint64_t inner, uint64_t outer, uint32_t bi, uint32_t bo, CUtensorMapSwizzle sw) {
  cuuint64_t dims[2] = {inner, outer}; cuuint64_t strides[1] = {inner * 2};
  cuuint32_t box[2] = {bi, bo}; cuuint32_t es[2] = {1, 1};
  enc(m, CU_TENSOR_MAP_DATA_TYPE_BFLOAT16, 2, const_cast<void*>(base), dims, strides, box, es, CU_TENSOR_MAP_INTERLEAVE_NONE, sw,
      CU_TENSOR_MAP_L2_PROMOTION_L2_128B, CU_TENSOR_MAP_FLOAT_OOB_FILL_NONE);
}

}

extern "C" void kernel_launch(void* const* d_in, const int* in_sizes, int n_in, void* d_out, int out_size) {
  static PFN_enc enc = nullptr;
  if (!enc) {
    void* fn = nullptr; cudaDriverEntryPointQueryResult qr;
    cudaGetDriverEntryPoint("cuTensorMapEncodeTiled", &fn, cudaEnableDefault, &qr);
    enc = (PFN_enc)fn;
    cudaFuncSetAttribute(fused_kernel, cudaFuncAttributeMaxDynamicSharedMemorySize, SMEM_BYTES);
  }
  Maps mp;
  const CUtensorMapSwizzle S128 = CU_TENSOR_MAP_SWIZZLE_128B, S64 = CU_TENSOR_MAP_SWIZZLE_64B;
  enc2d(enc, &mp.x, d_in[0], 448, 2048, 64, 128, S128);
  enc2d(enc, &mp.qkv, d_in[1], 1344, 448, 64, 64, S128);
  enc2d(enc, &mp.g, d_in[4], 1792, 448, 64, 64, S128);
  enc2d(enc, &mp.u, d_in[5], 1792, 448, 64, 64, S128);
  enc2d(enc, &mp.q32, d_in[1], 1344, 448, 32, 64, S64);
  enc2d(enc, &mp.q24, d_in[1], 1344, 448, 24, 64, S64);
  enc2d(enc, &mp.g32, d_in[4], 1792, 448, 32, 64, S64);
  enc2d(enc, &mp.u32, d_in[5], 1792, 448, 32, 64, S64);
  enc2d(enc, &mp.d, d_in[6], 448, 1792, 64, 64, S128);
  enc2d(enc, &mp.d32, d_in[6], 448, 1792, 64, 32, S128);
  enc2d(enc, &mp.o, d_in[2], 448, 448, 64, 64, S128);
  enc2d(enc, &mp.out, d_out, 448, 2048, 64, 64, S128);
  fused_kernel<<<128, 384, SMEM_BYTES>>>(mp, (const __nv_bfloat16*)d_in[0], (__nv_bfloat16*)d_out);
}
```

```cpp
#include <cuda_runtime.h>
#include <cuda.h>
#include <cuda_bf16.h>
#include <stdint.h>

#define WDELAY 2
#define W0POS 6
#define PFM 2
#define NG 2
#define NP 3
#define PFW 4
#define PFW2 11
#define PFK 2
#define NOUT 4
#define XWAIT 3
namespace {

constexpr int DM = 448;
constexpr uint32_t SB = 0x400;
constexpr uint32_t OFF_X = 0;
constexpr uint32_t OFF_SLOT = 7 * 16384;
constexpr uint32_t OFF_BAR = 14 * 16384;
constexpr uint32_t BAR_FULL = OFF_BAR;
constexpr uint32_t BAR_X = OFF_BAR + 1024;
constexpr uint32_t BAR_XW = OFF_BAR + 1080;
constexpr uint32_t BAR_XR = BAR_FULL + 8 * 7;
constexpr uint32_t BAR_TW = OFF_BAR + 1096;
constexpr uint32_t BAR_TILES = BAR_FULL + 8 * 15;
constexpr uint32_t BAR_KVP = OFF_BAR + 1112;
constexpr uint32_t BAR_KVB = BAR_FULL + 8 * 32;
constexpr uint32_t BAR_PAR = BAR_FULL + 8 * 13;
constexpr uint32_t BAR_E56 = BAR_FULL + 8 * 9;
constexpr uint32_t OFF_PAR = OFF_BAR + 1144;
constexpr uint32_t BAR_RDY = OFF_BAR + 1152;
constexpr uint32_t BAR_DAT = OFF_BAR + 1216;
constexpr uint32_t BAR_OW = OFF_BAR + 1472;
#define SMEM_BYTES (OFF_BAR + 1536 + TSB)
constexpr uint32_t OFF_KVB = OFF_SLOT + 6 * 16384 + 8192;
constexpr uint32_t BAR_XW2 = OFF_BAR + 1000, BAR_XR2 = BAR_FULL + 8 * 12;
constexpr uint32_t BAR_RDY2 = OFF_BAR + 1016;
constexpr int KVN = 21 * 128;

__device__ float g_kvsum[2 * 8 * KVN];
__device__ unsigned g_cnt[8 * 32];
__device__ unsigned g_cnt2[16 * 32];
#define STAMP(i)
#define STAMPW(i)
#define GSTAMP(v)
#define TSB 0

struct Maps { CUtensorMap x, qkv, q32, q24, g32, u32, g, u, d, d32, o, out; const char* w[5]; };

__host__ __device__ constexpr uint32_t buf_off(int t) {
  constexpr int t0[15] = {5, 0, 1, 3, 4, 2, 6, 5, 0, 1, 3, 4, 5, 0, 1};
  if (t < 15) return OFF_SLOT + t0[t] * 16384;
  if (t < 35) return OFF_SLOT + ((t - 12) % 6) * 16384;
  constexpr int tb[18] = {0, 26, 2, 24, 8, 10, 4, 27, 14, 22, 16, 18, 20, 0, 23, 2, 24, 4};
  return tb[t - 35] * 8192;
}
__host__ __device__ constexpr int ord_of(int i) { constexpr int tb[18] = {36, 35, 37, 38, 41, 39, 42, 40, 43, 45, 46, 47, 44, 49, 48, 50, 51, 52}; return tb[i]; }
__host__ __device__ constexpr int dep_of(int i) { constexpr int tb[18] = {0, 0, 29, 30, 31, 32, 0, 33, 0, 0, 0, 0, 34, 0, 37, 0, 41, 0}; return tb[i]; }

__device__ __forceinline__ uint32_t smem_u32(const void* p) { return (uint32_t)__cvta_generic_to_shared(p); }
__device__ __forceinline__ void mbar_init(uint32_t bar, uint32_t cnt) { asm volatile("mbarrier.init.shared::cta.b64 [%0], %1;" :: "r"(bar), "r"(cnt) : "memory"); }
__device__ __forceinline__ void mbar_expect_tx(uint32_t bar, uint32_t bytes) { asm volatile("mbarrier.arrive.expect_tx.shared::cta.b64 _, [%0], %1;" :: "r"(bar), "r"(bytes) : "memory"); }
__device__ __forceinline__ void mbar_arrive(uint32_t bar) { asm volatile("mbarrier.arrive.shared::cta.b64 _, [%0];" :: "r"(bar) : "memory"); }
__device__ __forceinline__ void mbar_arrive_pred(uint32_t bar, uint32_t pred) {
  asm volatile("{\n.reg .pred p;\nsetp.ne.u32 p, %1, 0;\n@p mbarrier.arrive.shared::cta.b64 _, [%0];\n}" :: "r"(bar), "r"(pred) : "memory");
}
__device__ __forceinline__ void mbar_wait_(uint32_t bar, uint32_t& budget) {
  asm volatile("{\n.reg .pred P1;\nLAB_WAIT:\n"
    "mbarrier.try_wait.parity.shared::cta.b64 P1, [%1], 0;\n"
    "add.u32 %0, %0, 1;\nsetp.lt.and.u32 P1, %0, 8000000, !P1;\n@P1 bra LAB_WAIT;\n}\n" : "+r"(budget) : "r"(bar) : "memory");
}
#define mbar_wait(bar) mbar_wait_(bar, budget)
__device__ __forceinline__ void tma2d(uint32_t dst, const CUtensorMap* m, uint32_t bar, int c0, int c1) {
  asm volatile("cp.async.bulk.tensor.2d.shared::cluster.global.mbarrier::complete_tx::bytes [%0], [%1, {%3, %4}], [%2];"
    :: "r"(dst), "l"(m), "r"(bar), "r"(c0), "r"(c1) : "memory");
}
__device__ __forceinline__ uint32_t elect_one() {
  uint32_t p; asm volatile("{\n.reg .pred P;\nelect.sync _|P, 0xffffffff;\nselp.u32 %0, 1, 0, P;\n}" : "=r"(p)); return p;
}
__device__ __forceinline__ int lane_id() { int l; asm volatile("mov.u32 %0, %%laneid;" : "=r"(l)); return l; }
__device__ __forceinline__ void prefetch_map(const CUtensorMap* m) { asm volatile("prefetch.tensormap [%0];" :: "l"(m) : "memory"); }
__device__ __forceinline__ void fence_async() { asm volatile("fence.proxy.async.shared::cta;" ::: "memory"); }
__device__ __forceinline__ void wg_fence() { asm volatile("wgmma.fence.sync.aligned;" ::: "memory"); }
__device__ __forceinline__ void wg_commit() { asm volatile("wgmma.commit_group.sync.aligned;" ::: "memory"); }
template<int N> __device__ __forceinline__ void wg_wait() { asm volatile("wgmma.wait_group.sync.aligned %0;" :: "n"(N) : "memory"); }
__host__ __device__ constexpr uint64_t make_desc(uint32_t addr, uint32_t lbo, uint32_t sbo, uint64_t swz) {
  return (uint64_t)((addr & 0x3FFFF) >> 4) | ((uint64_t)(lbo >> 4) << 16) | ((uint64_t)(sbo >> 4) << 32) | (swz << 62);
}
template<int LO, int HI, int N> __device__ __forceinline__ void fence_regs(float (&a)[N]) {
  #pragma unroll
  for (int i = LO; i < HI; i++) asm volatile("" : "+f"(a[i]) :: "memory");
}
__device__ __forceinline__ uint32_t pack2(float lo, float hi) { uint32_t r; asm("cvt.rn.bf16x2.f32 %0, %1, %2;" : "=r"(r) : "f"(hi), "f"(lo)); return r; }
__device__ __forceinline__ void ldsm4(uint32_t& a, uint32_t& b, uint32_t& c, uint32_t& d, uint32_t addr) {
  asm volatile("ldmatrix.sync.aligned.m8n8.x4.shared.b16 {%0, %1, %2, %3}, [%4];" : "=r"(a), "=r"(b), "=r"(c), "=r"(d) : "r"(addr) : "memory");
}
__device__ __forceinline__ void stsm4(uint32_t addr, uint32_t a, uint32_t b, uint32_t c, uint32_t d) {
  asm volatile("stmatrix.sync.aligned.m8n8.x4.shared.b16 [%0], {%1, %2, %3, %4};" :: "r"(addr), "r"(a), "r"(b), "r"(c), "r"(d) : "memory");
}
__device__ __forceinline__ void mma_rowsum(float (&c)[4], uint32_t a0, uint32_t a1, uint32_t a2, uint32_t a3) {
  asm volatile("mma.sync.aligned.m16n8k16.row.col.f32.bf16.bf16.f32 {%0,%1,%2,%3}, {%4,%5,%6,%7}, {%8,%8}, {%0,%1,%2,%3};"
    : "+f"(c[0]), "+f"(c[1]), "+f"(c[2]), "+f"(c[3]) : "r"(a0), "r"(a1), "r"(a2), "r"(a3), "r"(0x3F803F80u));
}
__device__ __forceinline__ uint32_t hsub2(uint32_t a, uint32_t b) { uint32_t r; asm("sub.rn.bf16x2 %0, %1, %2;" : "=r"(r) : "r"(a), "r"(b)); return r; }
__device__ __forceinline__ uint32_t hadd2(uint32_t a, uint32_t b) { uint32_t r; asm("add.rn.bf16x2 %0, %1, %2;" : "=r"(r) : "r"(a), "r"(b)); return r; }
__device__ __forceinline__ uint32_t hfma2(uint32_t a, uint32_t b, uint32_t c) { uint32_t r; asm("fma.rn.bf16x2 %0, %1, %2, %3;" : "=r"(r) : "r"(a), "r"(b), "r"(c)); return r; }
__device__ __forceinline__ void warp_arrive(uint32_t bar) {
  __syncwarp();
  asm volatile("{\n.reg .pred p;\nelect.sync _|p, 0xffffffff;\n@p mbarrier.arrive.shared::cta.b64 _, [%0];\n}" :: "r"(bar) : "memory");
}
__device__ __forceinline__ void pin2(uint32_t& a, uint32_t& b) {
  asm volatile("{\n.reg .u32 c;\nmov.u32 c, %%clock;\nlop3.b32 %0, %0, c, %2, 0xF8;\nlop3.b32 %1, %1, c, %2, 0xF8;\n}" : "+r"(a), "+r"(b) : "r"(blockIdx.y) : "memory");
}
__device__ __forceinline__ float bf_lo(uint32_t u) { return __uint_as_float(u << 16); }
__device__ __forceinline__ float bf_hi(uint32_t u) { return __uint_as_float(u & 0xFFFF0000u); }
__device__ __forceinline__ float bf_round(float x) { return bf_lo(pack2(x, 0.f)); }
__device__ __forceinline__ float ex2(float x) { float r; asm("ex2.approx.ftz.f32 %0, %1;" : "=f"(r) : "f"(x)); return r; }
__device__ __forceinline__ float rcp(float x) { float r; asm("rcp.approx.ftz.f32 %0, %1;" : "=f"(r) : "f"(x)); return r; }
__device__ __forceinline__ float sqrt_approx(float x) { float r; asm("sqrt.approx.ftz.f32 %0, %1;" : "=f"(r) : "f"(x)); return r; }
__device__ __forceinline__ uint32_t phi2(float a0, float a1, float r, float rl) {
  const float e0 = __saturatef(ex2(a0 * rl) + 1e-6f), e1 = __saturatef(ex2(a1 * rl) + 1e-6f);
  return pack2(fmaxf(fmaf(a0, r, 1.000001f), e0), fmaxf(fmaf(a1, r, 1.000001f), e1));
}
__device__ __forceinline__ float geglu1(float g, float u, float c0, float c1, float c2) {
  float t = fmaf(g * g, c1, c0) * g, th;
  asm("tanh.approx.f32 %0, %1;" : "=f"(th) : "f"(t));
  float hh = g * u * c2;
  return fmaf(hh, th, hh);
}

template<int SD, uint64_t AD, uint64_t BD, int SZ> __device__ __forceinline__ void wg_ss128(float (&d)[SZ], uint32_t aoff) {
  if constexpr (SD == 0)
  asm volatile("{\n.reg .pred p;\n.reg .b64 ad, bd;\n.reg .b32 lo;\nsetp.ne.b32 p, 0, 0;\n"
    "add.u32 lo, %64, %65;\nmov.b64 ad, {lo, %66};\n"
    "mov.b64 bd, %67;\n"
    "wgmma.mma_async.sync.aligned.m64n128k16.f32.bf16.bf16 "
    "{%0, %1, %2, %3, %4, %5, %6, %7, %8, %9, %10, %11, %12, %13, %14, %15, %16, %17, %18, %19, %20, %21, %22, %23, %24, %25, %26, %27, %28, %29, %30, %31, %32, %33, %34, %35, %36, %37, %38, %39, %40, %41, %42, %43, %44, %45, %46, %47, %48, %49, %50, %51, %52, %53, %54, %55, %56, %57, %58, %59, %60, %61, %62, %63}, "
    "ad, bd, p, 1, 1, 0, 1;\n}\n"
    : "=f"(d[0]), "=f"(d[1]), "=f"(d[2]), "=f"(d[3]), "=f"(d[4]), "=f"(d[5]), "=f"(d[6]), "=f"(d[7]), "=f"(d[8]), "=f"(d[9]), "=f"(d[10]), "=f"(d[11]), "=f"(d[12]), "=f"(d[13]), "=f"(d[14]), "=f"(d[15]), "=f"(d[16]), "=f"(d[17]), "=f"(d[18]), "=f"(d[19]), "=f"(d[20]), "=f"(d[21]), "=f"(d[22]), "=f"(d[23]), "=f"(d[24]), "=f"(d[25]), "=f"(d[26]), "=f"(d[27]), "=f"(d[28]), "=f"(d[29]), "=f"(d[30]), "=f"(d[31]), "=f"(d[32]), "=f"(d[33]), "=f"(d[34]), "=f"(d[35]), "=f"(d[36]), "=f"(d[37]), "=f"(d[38]), "=f"(d[39]), "=f"(d[40]), "=f"(d[41]), "=f"(d[42]), "=f"(d[43]), "=f"(d[44]), "=f"(d[45]), "=f"(d[46]), "=f"(d[47]), "=f"(d[48]), "=f"(d[49]), "=f"(d[50]), "=f"(d[51]), "=f"(d[52]), "=f"(d[53]), "=f"(d[54]), "=f"(d[55]), "=f"(d[56]), "=f"(d[57]), "=f"(d[58]), "=f"(d[59]), "=f"(d[60]), "=f"(d[61]), "=f"(d[62]), "=f"(d[63])
    : "r"(aoff), "n"((uint32_t)AD), "n"((uint32_t)(AD >> 32)), "n"(BD));
  if constexpr (SD == 1)
  asm volatile("{\n.reg .pred p;\n.reg .b64 ad, bd;\n.reg .b32 lo;\nsetp.ne.b32 p, 1, 0;\n"
    "add.u32 lo, %64, %65;\nmov.b64 ad, {lo, %66};\n"
    "mov.b64 bd, %67;\n"
    "wgmma.mma_async.sync.aligned.m64n128k16.f32.bf16.bf16 "
    "{%0, %1, %2, %3, %4, %5, %6, %7, %8, %9, %10, %11, %12, %13, %14, %15, %16, %17, %18, %19, %20, %21, %22, %23, %24, %25, %26, %27, %28, %29, %30, %31, %32, %33, %34, %35, %36, %37, %38, %39, %40, %41, %42, %43, %44, %45, %46, %47, %48, %49, %50, %51, %52, %53, %54, %55, %56, %57, %58, %59, %60, %61, %62, %63}, "
    "ad, bd, p, 1, 1, 0, 1;\n}\n"
    : "+f"(d[0]), "+f"(d[1]), "+f"(d[2]), "+f"(d[3]), "+f"(d[4]), "+f"(d[5]), "+f"(d[6]), "+f"(d[7]), "+f"(d[8]), "+f"(d[9]), "+f"(d[10]), "+f"(d[11]), "+f"(d[12]), "+f"(d[13]), "+f"(d[14]), "+f"(d[15]), "+f"(d[16]), "+f"(d[17]), "+f"(d[18]), "+f"(d[19]), "+f"(d[20]), "+f"(d[21]), "+f"(d[22]), "+f"(d[23]), "+f"(d[24]), "+f"(d[25]), "+f"(d[26]), "+f"(d[27]), "+f"(d[28]), "+f"(d[29]), "+f"(d[30]), "+f"(d[31]), "+f"(d[32]), "+f"(d[33]), "+f"(d[34]), "+f"(d[35]), "+f"(d[36]), "+f"(d[37]), "+f"(d[38]), "+f"(d[39]), "+f"(d[40]), "+f"(d[41]), "+f"(d[42]), "+f"(d[43]), "+f"(d[44]), "+f"(d[45]), "+f"(d[46]), "+f"(d[47]), "+f"(d[48]), "+f"(d[49]), "+f"(d[50]), "+f"(d[51]), "+f"(d[52]), "+f"(d[53]), "+f"(d[54]), "+f"(d[55]), "+f"(d[56]), "+f"(d[57]), "+f"(d[58]), "+f"(d[59]), "+f"(d[60]), "+f"(d[61]), "+f"(d[62]), "+f"(d[63])
    : "r"(aoff), "n"((uint32_t)AD), "n"((uint32_t)(AD >> 32)), "n"(BD));
}
template<int SD, uint64_t AD, uint64_t BD, int SZ> __device__ __forceinline__ void wg_ss120(float (&d)[SZ], uint32_t aoff) {
  if constexpr (SD == 0)
  asm volatile("{\n.reg .pred p;\n.reg .b64 ad, bd;\n.reg .b32 lo;\nsetp.ne.b32 p, 0, 0;\n"
    "add.u32 lo, %60, %61;\nmov.b64 ad, {lo, %62};\n"
    "mov.b64 bd, %63;\n"
    "wgmma.mma_async.sync.aligned.m64n120k16.f32.bf16.bf16 "
    "{%0, %1, %2, %3, %4, %5, %6, %7, %8, %9, %10, %11, %12, %13, %14, %15, %16, %17, %18, %19, %20, %21, %22, %23, %24, %25, %26, %27, %28, %29, %30, %31, %32, %33, %34, %35, %36, %37, %38, %39, %40, %41, %42, %43, %44, %45, %46, %47, %48, %49, %50, %51, %52, %53, %54, %55, %56, %57, %58, %59}, "
    "ad, bd, p, 1, 1, 0, 1;\n}\n"
    : "=f"(d[0]), "=f"(d[1]), "=f"(d[2]), "=f"(d[3]), "=f"(d[4]), "=f"(d[5]), "=f"(d[6]), "=f"(d[7]), "=f"(d[8]), "=f"(d[9]), "=f"(d[10]), "=f"(d[11]), "=f"(d[12]), "=f"(d[13]), "=f"(d[14]), "=f"(d[15]), "=f"(d[16]), "=f"(d[17]), "=f"(d[18]), "=f"(d[19]), "=f"(d[20]), "=f"(d[21]), "=f"(d[22]), "=f"(d[23]), "=f"(d[24]), "=f"(d[25]), "=f"(d[26]), "=f"(d[27]), "=f"(d[28]), "=f"(d[29]), "=f"(d[30]), "=f"(d[31]), "=f"(d[32]), "=f"(d[33]), "=f"(d[34]), "=f"(d[35]), "=f"(d[36]), "=f"(d[37]), "=f"(d[38]), "=f"(d[39]), "=f"(d[40]), "=f"(d[41]), "=f"(d[42]), "=f"(d[43]), "=f"(d[44]), "=f"(d[45]), "=f"(d[46]), "=f"(d[47]), "=f"(d[48]), "=f"(d[49]), "=f"(d[50]), "=f"(d[51]), "=f"(d[52]), "=f"(d[53]), "=f"(d[54]), "=f"(d[55]), "=f"(d[56]), "=f"(d[57]), "=f"(d[58]), "=f"(d[59])
    : "r"(aoff), "n"((uint32_t)AD), "n"((uint32_t)(AD >> 32)), "n"(BD));
  if constexpr (SD == 1)
  asm volatile("{\n.reg .pred p;\n.reg .b64 ad, bd;\n.reg .b32 lo;\nsetp.ne.b32 p, 1, 0;\n"
    "add.u32 lo, %60, %61;\nmov.b64 ad, {lo, %62};\n"
    "mov.b64 bd, %63;\n"
    "wgmma.mma_async.sync.aligned.m64n120k16.f32.bf16.bf16 "
    "{%0, %1, %2, %3, %4, %5, %6, %7, %8, %9, %10, %11, %12, %13, %14, %15, %16, %17, %18, %19, %20, %21, %22, %23, %24, %25, %26, %27, %28, %29, %30, %31, %32, %33, %34, %35, %36, %37, %38, %39, %40, %41, %42, %43, %44, %45, %46, %47, %48, %49, %50, %51, %52, %53, %54, %55, %56, %57, %58, %59}, "
    "ad, bd, p, 1, 1, 0, 1;\n}\n"
    : "+f"(d[0]), "+f"(d[1]), "+f"(d[2]), "+f"(d[3]), "+f"(d[4]), "+f"(d[5]), "+f"(d[6]), "+f"(d[7]), "+f"(d[8]), "+f"(d[9]), "+f"(d[10]), "+f"(d[11]), "+f"(d[12]), "+f"(d[13]), "+f"(d[14]), "+f"(d[15]), "+f"(d[16]), "+f"(d[17]), "+f"(d[18]), "+f"(d[19]), "+f"(d[20]), "+f"(d[21]), "+f"(d[22]), "+f"(d[23]), "+f"(d[24]), "+f"(d[25]), "+f"(d[26]), "+f"(d[27]), "+f"(d[28]), "+f"(d[29]), "+f"(d[30]), "+f"(d[31]), "+f"(d[32]), "+f"(d[33]), "+f"(d[34]), "+f"(d[35]), "+f"(d[36]), "+f"(d[37]), "+f"(d[38]), "+f"(d[39]), "+f"(d[40]), "+f"(d[41]), "+f"(d[42]), "+f"(d[43]), "+f"(d[44]), "+f"(d[45]), "+f"(d[46]), "+f"(d[47]), "+f"(d[48]), "+f"(d[49]), "+f"(d[50]), "+f"(d[51]), "+f"(d[52]), "+f"(d[53]), "+f"(d[54]), "+f"(d[55]), "+f"(d[56]), "+f"(d[57]), "+f"(d[58]), "+f"(d[59])
    : "r"(aoff), "n"((uint32_t)AD), "n"((uint32_t)(AD >> 32)), "n"(BD));
}
template<int SD, uint64_t AD, uint64_t BD, int SZ> __device__ __forceinline__ void wg_ss40t(float (&d)[SZ], uint32_t aoff) {
  if constexpr (SD == 0)
  asm volatile("{\n.reg .pred p;\n.reg .b64 ad, bd;\n.reg .b32 lo;\nsetp.ne.b32 p, 0, 0;\n"
    "mov.u32 lo, %21;\nmov.b64 ad, {lo, %22};\n"
    "add.u32 lo, %20, %23;\nmov.b64 bd, {lo, %24};\n"
    "wgmma.mma_async.sync.aligned.m64n40k16.f32.bf16.bf16 "
    "{%0, %1, %2, %3, %4, %5, %6, %7, %8, %9, %10, %11, %12, %13, %14, %15, %16, %17, %18, %19}, "
    "ad, bd, p, 1, 1, 1, 1;\n}\n"
    : "=f"(d[0]), "=f"(d[1]), "=f"(d[2]), "=f"(d[3]), "=f"(d[4]), "=f"(d[5]), "=f"(d[6]), "=f"(d[7]), "=f"(d[8]), "=f"(d[9]), "=f"(d[10]), "=f"(d[11]), "=f"(d[12]), "=f"(d[13]), "=f"(d[14]), "=f"(d[15]), "=f"(d[16]), "=f"(d[17]), "=f"(d[18]), "=f"(d[19])
    : "r"(aoff), "n"((uint32_t)AD), "n"((uint32_t)(AD >> 32)), "n"((uint32_t)BD), "n"((uint32_t)(BD >> 32)));
  if constexpr (SD == 1)
  asm volatile("{\n.reg .pred p;\n.reg .b64 ad, bd;\n.reg .b32 lo;\nsetp.ne.b32 p, 1, 0;\n"
    "mov.u32 lo, %21;\nmov.b64 ad, {lo, %22};\n"
    "add.u32 lo, %20, %23;\nmov.b64 bd, {lo, %24};\n"
    "wgmma.mma_async.sync.aligned.m64n40k16.f32.bf16.bf16 "
    "{%0, %1, %2, %3, %4, %5, %6, %7, %8, %9, %10, %11, %12, %13, %14, %15, %16, %17, %18, %19}, "
    "ad, bd, p, 1, 1, 1, 1;\n}\n"
    : "+f"(d[0]), "+f"(d[1]), "+f"(d[2]), "+f"(d[3]), "+f"(d[4]), "+f"(d[5]), "+f"(d[6]), "+f"(d[7]), "+f"(d[8]), "+f"(d[9]), "+f"(d[10]), "+f"(d[11]), "+f"(d[12]), "+f"(d[13]), "+f"(d[14]), "+f"(d[15]), "+f"(d[16]), "+f"(d[17]), "+f"(d[18]), "+f"(d[19])
    : "r"(aoff), "n"((uint32_t)AD), "n"((uint32_t)(AD >> 32)), "n"((uint32_t)BD), "n"((uint32_t)(BD >> 32)));
}
template<int SD, uint64_t BD, int SZ> __device__ __forceinline__ void wg_rs128(float (&d)[SZ], uint32_t a0, uint32_t a1, uint32_t a2, uint32_t a3) {
  if constexpr (SD == 0)
  asm volatile("{\n.reg .pred p;\n.reg .b64 ad, bd;\n.reg .b32 lo;\nsetp.ne.b32 p, 0, 0;\n"
    "mov.b64 bd, %68;\n"
    "wgmma.mma_async.sync.aligned.m64n128k16.f32.bf16.bf16 "
    "{%0, %1, %2, %3, %4, %5, %6, %7, %8, %9, %10, %11, %12, %13, %14, %15, %16, %17, %18, %19, %20, %21, %22, %23, %24, %25, %26, %27, %28, %29, %30, %31, %32, %33, %34, %35, %36, %37, %38, %39, %40, %41, %42, %43, %44, %45, %46, %47, %48, %49, %50, %51, %52, %53, %54, %55, %56, %57, %58, %59, %60, %61, %62, %63}, "
    "{%64, %65, %66, %67}, bd, p, 1, 1, 1;\n}\n"
    : "=f"(d[0]), "=f"(d[1]), "=f"(d[2]), "=f"(d[3]), "=f"(d[4]), "=f"(d[5]), "=f"(d[6]), "=f"(d[7]), "=f"(d[8]), "=f"(d[9]), "=f"(d[10]), "=f"(d[11]), "=f"(d[12]), "=f"(d[13]), "=f"(d[14]), "=f"(d[15]), "=f"(d[16]), "=f"(d[17]), "=f"(d[18]), "=f"(d[19]), "=f"(d[20]), "=f"(d[21]), "=f"(d[22]), "=f"(d[23]), "=f"(d[24]), "=f"(d[25]), "=f"(d[26]), "=f"(d[27]), "=f"(d[28]), "=f"(d[29]), "=f"(d[30]), "=f"(d[31]), "=f"(d[32]), "=f"(d[33]), "=f"(d[34]), "=f"(d[35]), "=f"(d[36]), "=f"(d[37]), "=f"(d[38]), "=f"(d[39]), "=f"(d[40]), "=f"(d[41]), "=f"(d[42]), "=f"(d[43]), "=f"(d[44]), "=f"(d[45]), "=f"(d[46]), "=f"(d[47]), "=f"(d[48]), "=f"(d[49]), "=f"(d[50]), "=f"(d[51]), "=f"(d[52]), "=f"(d[53]), "=f"(d[54]), "=f"(d[55]), "=f"(d[56]), "=f"(d[57]), "=f"(d[58]), "=f"(d[59]), "=f"(d[60]), "=f"(d[61]), "=f"(d[62]), "=f"(d[63])
    : "r"(a0), "r"(a1), "r"(a2), "r"(a3), "n"(BD));
  if constexpr (SD == 1)
  asm volatile("{\n.reg .pred p;\n.reg .b64 ad, bd;\n.reg .b32 lo;\nsetp.ne.b32 p, 1, 0;\n"
    "mov.b64 bd, %68;\n"
    "wgmma.mma_async.sync.aligned.m64n128k16.f32.bf16.bf16 "
    "{%0, %1, %2, %3, %4, %5, %6, %7, %8, %9, %10, %11, %12, %13, %14, %15, %16, %17, %18, %19, %20, %21, %22, %23, %24, %25, %26, %27, %28, %29, %30, %31, %32, %33, %34, %35, %36, %37, %38, %39, %40, %41, %42, %43, %44, %45, %46, %47, %48, %49, %50, %51, %52, %53, %54, %55, %56, %57, %58, %59, %60, %61, %62, %63}, "
    "{%64, %65, %66, %67}, bd, p, 1, 1, 1;\n}\n"
    : "+f"(d[0]), "+f"(d[1]), "+f"(d[2]), "+f"(d[3]), "+f"(d[4]), "+f"(d[5]), "+f"(d[6]), "+f"(d[7]), "+f"(d[8]), "+f"(d[9]), "+f"(d[10]), "+f"(d[11]), "+f"(d[12]), "+f"(d[13]), "+f"(d[14]), "+f"(d[15]), "+f"(d[16]), "+f"(d[17]), "+f"(d[18]), "+f"(d[19]), "+f"(d[20]), "+f"(d[21]), "+f"(d[22]), "+f"(d[23]), "+f"(d[24]), "+f"(d[25]), "+f"(d[26]), "+f"(d[27]), "+f"(d[28]), "+f"(d[29]), "+f"(d[30]), "+f"(d[31]), "+f"(d[32]), "+f"(d[33]), "+f"(d[34]), "+f"(d[35]), "+f"(d[36]), "+f"(d[37]), "+f"(d[38]), "+f"(d[39]), "+f"(d[40]), "+f"(d[41]), "+f"(d[42]), "+f"(d[43]), "+f"(d[44]), "+f"(d[45]), "+f"(d[46]), "+f"(d[47]), "+f"(d[48]), "+f"(d[49]), "+f"(d[50]), "+f"(d[51]), "+f"(d[52]), "+f"(d[53]), "+f"(d[54]), "+f"(d[55]), "+f"(d[56]), "+f"(d[57]), "+f"(d[58]), "+f"(d[59]), "+f"(d[60]), "+f"(d[61]), "+f"(d[62]), "+f"(d[63])
    : "r"(a0), "r"(a1), "r"(a2), "r"(a3), "n"(BD));
}
template<int SD, uint64_t BD, int SZ> __device__ __forceinline__ void wg_rs120(float (&d)[SZ], uint32_t a0, uint32_t a1, uint32_t a2, uint32_t a3, uint32_t boff) {
  if constexpr (SD == 0)
  asm volatile("{\n.reg .pred p;\n.reg .b64 ad, bd;\n.reg .b32 lo;\nsetp.ne.b32 p, 0, 0;\n"
    "add.u32 lo, %64, %65;\nmov.b64 bd, {lo, %66};\n"
    "wgmma.mma_async.sync.aligned.m64n120k16.f32.bf16.bf16 "
    "{%0, %1, %2, %3, %4, %5, %6, %7, %8, %9, %10, %11, %12, %13, %14, %15, %16, %17, %18, %19, %20, %21, %22, %23, %24, %25, %26, %27, %28, %29, %30, %31, %32, %33, %34, %35, %36, %37, %38, %39, %40, %41, %42, %43, %44, %45, %46, %47, %48, %49, %50, %51, %52, %53, %54, %55, %56, %57, %58, %59}, "
    "{%60, %61, %62, %63}, bd, p, 1, 1, 1;\n}\n"
    : "=f"(d[0]), "=f"(d[1]), "=f"(d[2]), "=f"(d[3]), "=f"(d[4]), "=f"(d[5]), "=f"(d[6]), "=f"(d[7]), "=f"(d[8]), "=f"(d[9]), "=f"(d[10]), "=f"(d[11]), "=f"(d[12]), "=f"(d[13]), "=f"(d[14]), "=f"(d[15]), "=f"(d[16]), "=f"(d[17]), "=f"(d[18]), "=f"(d[19]), "=f"(d[20]), "=f"(d[21]), "=f"(d[22]), "=f"(d[23]), "=f"(d[24]), "=f"(d[25]), "=f"(d[26]), "=f"(d[27]), "=f"(d[28]), "=f"(d[29]), "=f"(d[30]), "=f"(d[31]), "=f"(d[32]), "=f"(d[33]), "=f"(d[34]), "=f"(d[35]), "=f"(d[36]), "=f"(d[37]), "=f"(d[38]), "=f"(d[39]), "=f"(d[40]), "=f"(d[41]), "=f"(d[42]), "=f"(d[43]), "=f"(d[44]), "=f"(d[45]), "=f"(d[46]), "=f"(d[47]), "=f"(d[48]), "=f"(d[49]), "=f"(d[50]), "=f"(d[51]), "=f"(d[52]), "=f"(d[53]), "=f"(d[54]), "=f"(d[55]), "=f"(d[56]), "=f"(d[57]), "=f"(d[58]), "=f"(d[59])
    : "r"(a0), "r"(a1), "r"(a2), "r"(a3), "r"(boff), "n"((uint32_t)BD), "n"((uint32_t)(BD >> 32)));
  if constexpr (SD == 1)
  asm volatile("{\n.reg .pred p;\n.reg .b64 ad, bd;\n.reg .b32 lo;\nsetp.ne.b32 p, 1, 0;\n"
    "add.u32 lo, %64, %65;\nmov.b64 bd, {lo, %66};\n"
    "wgmma.mma_async.sync.aligned.m64n120k16.f32.bf16.bf16 "
    "{%0, %1, %2, %3, %4, %5, %6, %7, %8, %9, %10, %11, %12, %13, %14, %15, %16, %17, %18, %19, %20, %21, %22, %23, %24, %25, %26, %27, %28, %29, %30, %31, %32, %33, %34, %35, %36, %37, %38, %39, %40, %41, %42, %43, %44, %45, %46, %47, %48, %49, %50, %51, %52, %53, %54, %55, %56, %57, %58, %59}, "
    "{%60, %61, %62, %63}, bd, p, 1, 1, 1;\n}\n"
    : "+f"(d[0]), "+f"(d[1]), "+f"(d[2]), "+f"(d[3]), "+f"(d[4]), "+f"(d[5]), "+f"(d[6]), "+f"(d[7]), "+f"(d[8]), "+f"(d[9]), "+f"(d[10]), "+f"(d[11]), "+f"(d[12]), "+f"(d[13]), "+f"(d[14]), "+f"(d[15]), "+f"(d[16]), "+f"(d[17]), "+f"(d[18]), "+f"(d[19]), "+f"(d[20]), "+f"(d[21]), "+f"(d[22]), "+f"(d[23]), "+f"(d[24]), "+f"(d[25]), "+f"(d[26]), "+f"(d[27]), "+f"(d[28]), "+f"(d[29]), "+f"(d[30]), "+f"(d[31]), "+f"(d[32]), "+f"(d[33]), "+f"(d[34]), "+f"(d[35]), "+f"(d[36]), "+f"(d[37]), "+f"(d[38]), "+f"(d[39]), "+f"(d[40]), "+f"(d[41]), "+f"(d[42]), "+f"(d[43]), "+f"(d[44]), "+f"(d[45]), "+f"(d[46]), "+f"(d[47]), "+f"(d[48]), "+f"(d[49]), "+f"(d[50]), "+f"(d[51]), "+f"(d[52]), "+f"(d[53]), "+f"(d[54]), "+f"(d[55]), "+f"(d[56]), "+f"(d[57]), "+f"(d[58]), "+f"(d[59])
    : "r"(a0), "r"(a1), "r"(a2), "r"(a3), "r"(boff), "n"((uint32_t)BD), "n"((uint32_t)(BD >> 32)));
}
template<int SD, uint64_t AD, uint64_t BD, int SZ> __device__ __forceinline__ void wg_ss120b(float (&d)[SZ], uint32_t aoff, uint32_t boff) {
  if constexpr (SD == 0)
  asm volatile("{\n.reg .pred p;\n.reg .b64 ad, bd;\n.reg .b32 lo;\nsetp.ne.b32 p, 0, 0;\n"
    "add.u32 lo, %60, %61;\nmov.b64 ad, {lo, %62};\n"
    "add.u32 lo, %63, %64;\nmov.b64 bd, {lo, %65};\n"
    "wgmma.mma_async.sync.aligned.m64n120k16.f32.bf16.bf16 "
    "{%0, %1, %2, %3, %4, %5, %6, %7, %8, %9, %10, %11, %12, %13, %14, %15, %16, %17, %18, %19, %20, %21, %22, %23, %24, %25, %26, %27, %28, %29, %30, %31, %32, %33, %34, %35, %36, %37, %38, %39, %40, %41, %42, %43, %44, %45, %46, %47, %48, %49, %50, %51, %52, %53, %54, %55, %56, %57, %58, %59}, "
    "ad, bd, p, 1, 1, 0, 1;\n}\n"
    : "=f"(d[0]), "=f"(d[1]), "=f"(d[2]), "=f"(d[3]), "=f"(d[4]), "=f"(d[5]), "=f"(d[6]), "=f"(d[7]), "=f"(d[8]), "=f"(d[9]), "=f"(d[10]), "=f"(d[11]), "=f"(d[12]), "=f"(d[13]), "=f"(d[14]), "=f"(d[15]), "=f"(d[16]), "=f"(d[17]), "=f"(d[18]), "=f"(d[19]), "=f"(d[20]), "=f"(d[21]), "=f"(d[22]), "=f"(d[23]), "=f"(d[24]), "=f"(d[25]), "=f"(d[26]), "=f"(d[27]), "=f"(d[28]), "=f"(d[29]), "=f"(d[30]), "=f"(d[31]), "=f"(d[32]), "=f"(d[33]), "=f"(d[34]), "=f"(d[35]), "=f"(d[36]), "=f"(d[37]), "=f"(d[38]), "=f"(d[39]), "=f"(d[40]), "=f"(d[41]), "=f"(d[42]), "=f"(d[43]), "=f"(d[44]), "=f"(d[45]), "=f"(d[46]), "=f"(d[47]), "=f"(d[48]), "=f"(d[49]), "=f"(d[50]), "=f"(d[51]), "=f"(d[52]), "=f"(d[53]), "=f"(d[54]), "=f"(d[55]), "=f"(d[56]), "=f"(d[57]), "=f"(d[58]), "=f"(d[59])
    : "r"(aoff), "n"((uint32_t)AD), "n"((uint32_t)(AD >> 32)), "r"(boff), "n"((uint32_t)BD), "n"((uint32_t)(BD >> 32)));
  if constexpr (SD == 1)
  asm volatile("{\n.reg .pred p;\n.reg .b64 ad, bd;\n.reg .b32 lo;\nsetp.ne.b32 p, 1, 0;\n"
    "add.u32 lo, %60, %61;\nmov.b64 ad, {lo, %62};\n"
    "add.u32 lo, %63, %64;\nmov.b64 bd, {lo, %65};\n"
    "wgmma.mma_async.sync.aligned.m64n120k16.f32.bf16.bf16 "
    "{%0, %1, %2, %3, %4, %5, %6, %7, %8, %9, %10, %11, %12, %13, %14, %15, %16, %17, %18, %19, %20, %21, %22, %23, %24, %25, %26, %27, %28, %29, %30, %31, %32, %33, %34, %35, %36, %37, %38, %39, %40, %41, %42, %43, %44, %45, %46, %47, %48, %49, %50, %51, %52, %53, %54, %55, %56, %57, %58, %59}, "
    "ad, bd, p, 1, 1, 0, 1;\n}\n"
    : "+f"(d[0]), "+f"(d[1]), "+f"(d[2]), "+f"(d[3]), "+f"(d[4]), "+f"(d[5]), "+f"(d[6]), "+f"(d[7]), "+f"(d[8]), "+f"(d[9]), "+f"(d[10]), "+f"(d[11]), "+f"(d[12]), "+f"(d[13]), "+f"(d[14]), "+f"(d[15]), "+f"(d[16]), "+f"(d[17]), "+f"(d[18]), "+f"(d[19]), "+f"(d[20]), "+f"(d[21]), "+f"(d[22]), "+f"(d[23]), "+f"(d[24]), "+f"(d[25]), "+f"(d[26]), "+f"(d[27]), "+f"(d[28]), "+f"(d[29]), "+f"(d[30]), "+f"(d[31]), "+f"(d[32]), "+f"(d[33]), "+f"(d[34]), "+f"(d[35]), "+f"(d[36]), "+f"(d[37]), "+f"(d[38]), "+f"(d[39]), "+f"(d[40]), "+f"(d[41]), "+f"(d[42]), "+f"(d[43]), "+f"(d[44]), "+f"(d[45]), "+f"(d[46]), "+f"(d[47]), "+f"(d[48]), "+f"(d[49]), "+f"(d[50]), "+f"(d[51]), "+f"(d[52]), "+f"(d[53]), "+f"(d[54]), "+f"(d[55]), "+f"(d[56]), "+f"(d[57]), "+f"(d[58]), "+f"(d[59])
    : "r"(aoff), "n"((uint32_t)AD), "n"((uint32_t)(AD >> 32)), "r"(boff), "n"((uint32_t)BD), "n"((uint32_t)(BD >> 32)));
}
template<int SD, uint64_t BD, int SZ> __device__ __forceinline__ void wg_rs64(float (&d)[SZ], uint32_t a0, uint32_t a1, uint32_t a2, uint32_t a3) {
  if constexpr (SD == 0)
  asm volatile("{\n.reg .pred p;\n.reg .b64 ad, bd;\n.reg .b32 lo;\nsetp.ne.b32 p, 0, 0;\n"
    "mov.b64 bd, %36;\n"
    "wgmma.mma_async.sync.aligned.m64n64k16.f32.bf16.bf16 "
    "{%0, %1, %2, %3, %4, %5, %6, %7, %8, %9, %10, %11, %12, %13, %14, %15, %16, %17, %18, %19, %20, %21, %22, %23, %24, %25, %26, %27, %28, %29, %30, %31}, "
    "{%32, %33, %34, %35}, bd, p, 1, 1, 1;\n}\n"
    : "=f"(d[0]), "=f"(d[1]), "=f"(d[2]), "=f"(d[3]), "=f"(d[4]), "=f"(d[5]), "=f"(d[6]), "=f"(d[7]), "=f"(d[8]), "=f"(d[9]), "=f"(d[10]), "=f"(d[11]), "=f"(d[12]), "=f"(d[13]), "=f"(d[14]), "=f"(d[15]), "=f"(d[16]), "=f"(d[17]), "=f"(d[18]), "=f"(d[19]), "=f"(d[20]), "=f"(d[21]), "=f"(d[22]), "=f"(d[23]), "=f"(d[24]), "=f"(d[25]), "=f"(d[26]), "=f"(d[27]), "=f"(d[28]), "=f"(d[29]), "=f"(d[30]), "=f"(d[31])
    : "r"(a0), "r"(a1), "r"(a2), "r"(a3), "n"(BD));
  if constexpr (SD == 1)
  asm volatile("{\n.reg .pred p;\n.reg .b64 ad, bd;\n.reg .b32 lo;\nsetp.ne.b32 p, 1, 0;\n"
    "mov.b64 bd, %36;\n"
    "wgmma.mma_async.sync.aligned.m64n64k16.f32.bf16.bf16 "
    "{%0, %1, %2, %3, %4, %5, %6, %7, %8, %9, %10, %11, %12, %13, %14, %15, %16, %17, %18, %19, %20, %21, %22, %23, %24, %25, %26, %27, %28, %29, %30, %31}, "
    "{%32, %33, %34, %35}, bd, p, 1, 1, 1;\n}\n"
    : "+f"(d[0]), "+f"(d[1]), "+f"(d[2]), "+f"(d[3]), "+f"(d[4]), "+f"(d[5]), "+f"(d[6]), "+f"(d[7]), "+f"(d[8]), "+f"(d[9]), "+f"(d[10]), "+f"(d[11]), "+f"(d[12]), "+f"(d[13]), "+f"(d[14]), "+f"(d[15]), "+f"(d[16]), "+f"(d[17]), "+f"(d[18]), "+f"(d[19]), "+f"(d[20]), "+f"(d[21]), "+f"(d[22]), "+f"(d[23]), "+f"(d[24]), "+f"(d[25]), "+f"(d[26]), "+f"(d[27]), "+f"(d[28]), "+f"(d[29]), "+f"(d[30]), "+f"(d[31])
    : "r"(a0), "r"(a1), "r"(a2), "r"(a3), "n"(BD));
}
template<int SD, uint64_t BD, int SZ> __device__ __forceinline__ void wg_rs64h(float (&d)[SZ], uint32_t a0, uint32_t a1, uint32_t a2, uint32_t a3) {
  if constexpr (SD == 0)
  asm volatile("{\n.reg .pred p;\n.reg .b64 ad, bd;\n.reg .b32 lo;\nsetp.ne.b32 p, 0, 0;\n"
    "mov.b64 bd, %36;\n"
    "wgmma.mma_async.sync.aligned.m64n64k16.f32.bf16.bf16 "
    "{%0, %1, %2, %3, %4, %5, %6, %7, %8, %9, %10, %11, %12, %13, %14, %15, %16, %17, %18, %19, %20, %21, %22, %23, %24, %25, %26, %27, %28, %29, %30, %31}, "
    "{%32, %33, %34, %35}, bd, p, 1, 1, 1;\n}\n"
    : "=f"(d[32]), "=f"(d[33]), "=f"(d[34]), "=f"(d[35]), "=f"(d[36]), "=f"(d[37]), "=f"(d[38]), "=f"(d[39]), "=f"(d[40]), "=f"(d[41]), "=f"(d[42]), "=f"(d[43]), "=f"(d[44]), "=f"(d[45]), "=f"(d[46]), "=f"(d[47]), "=f"(d[48]), "=f"(d[49]), "=f"(d[50]), "=f"(d[51]), "=f"(d[52]), "=f"(d[53]), "=f"(d[54]), "=f"(d[55]), "=f"(d[56]), "=f"(d[57]), "=f"(d[58]), "=f"(d[59]), "=f"(d[60]), "=f"(d[61]), "=f"(d[62]), "=f"(d[63])
    : "r"(a0), "r"(a1), "r"(a2), "r"(a3), "n"(BD));
  if constexpr (SD == 1)
  asm volatile("{\n.reg .pred p;\n.reg .b64 ad, bd;\n.reg .b32 lo;\nsetp.ne.b32 p, 1, 0;\n"
    "mov.b64 bd, %36;\n"
    "wgmma.mma_async.sync.aligned.m64n64k16.f32.bf16.bf16 "
    "{%0, %1, %2, %3, %4, %5, %6, %7, %8, %9, %10, %11, %12, %13, %14, %15, %16, %17, %18, %19, %20, %21, %22, %23, %24, %25, %26, %27, %28, %29, %30, %31}, "
    "{%32, %33, %34, %35}, bd, p, 1, 1, 1;\n}\n"
    : "+f"(d[32]), "+f"(d[33]), "+f"(d[34]), "+f"(d[35]), "+f"(d[36]), "+f"(d[37]), "+f"(d[38]), "+f"(d[39]), "+f"(d[40]), "+f"(d[41]), "+f"(d[42]), "+f"(d[43]), "+f"(d[44]), "+f"(d[45]), "+f"(d[46]), "+f"(d[47]), "+f"(d[48]), "+f"(d[49]), "+f"(d[50]), "+f"(d[51]), "+f"(d[52]), "+f"(d[53]), "+f"(d[54]), "+f"(d[55]), "+f"(d[56]), "+f"(d[57]), "+f"(d[58]), "+f"(d[59]), "+f"(d[60]), "+f"(d[61]), "+f"(d[62]), "+f"(d[63])
    : "r"(a0), "r"(a1), "r"(a2), "r"(a3), "n"(BD));
}
template<int SD, uint64_t AD, uint64_t BD, int SZ> __device__ __forceinline__ void wg_ss64(float (&d)[SZ], uint32_t aoff) {
  if constexpr (SD == 0)
  asm volatile("{\n.reg .pred p;\n.reg .b64 ad, bd;\n.reg .b32 lo;\nsetp.ne.b32 p, 0, 0;\n"
    "add.u32 lo, %32, %33;\nmov.b64 ad, {lo, %34};\n"
    "mov.b64 bd, %35;\n"
    "wgmma.mma_async.sync.aligned.m64n64k16.f32.bf16.bf16 "
    "{%0, %1, %2, %3, %4, %5, %6, %7, %8, %9, %10, %11, %12, %13, %14, %15, %16, %17, %18, %19, %20, %21, %22, %23, %24, %25, %26, %27, %28, %29, %30, %31}, "
    "ad, bd, p, 1, 1, 0, 1;\n}\n"
    : "=f"(d[0]), "=f"(d[1]), "=f"(d[2]), "=f"(d[3]), "=f"(d[4]), "=f"(d[5]), "=f"(d[6]), "=f"(d[7]), "=f"(d[8]), "=f"(d[9]), "=f"(d[10]), "=f"(d[11]), "=f"(d[12]), "=f"(d[13]), "=f"(d[14]), "=f"(d[15]), "=f"(d[16]), "=f"(d[17]), "=f"(d[18]), "=f"(d[19]), "=f"(d[20]), "=f"(d[21]), "=f"(d[22]), "=f"(d[23]), "=f"(d[24]), "=f"(d[25]), "=f"(d[26]), "=f"(d[27]), "=f"(d[28]), "=f"(d[29]), "=f"(d[30]), "=f"(d[31])
    : "r"(aoff), "n"((uint32_t)AD), "n"((uint32_t)(AD >> 32)), "n"(BD));
  if constexpr (SD == 1)
  asm volatile("{\n.reg .pred p;\n.reg .b64 ad, bd;\n.reg .b32 lo;\nsetp.ne.b32 p, 1, 0;\n"
    "add.u32 lo, %32, %33;\nmov.b64 ad, {lo, %34};\n"
    "mov.b64 bd, %35;\n"
    "wgmma.mma_async.sync.aligned.m64n64k16.f32.bf16.bf16 "
    "{%0, %1, %2, %3, %4, %5, %6, %7, %8, %9, %10, %11, %12, %13, %14, %15, %16, %17, %18, %19, %20, %21, %22, %23, %24, %25, %26, %27, %28, %29, %30, %31}, "
    "ad, bd, p, 1, 1, 0, 1;\n}\n"
    : "+f"(d[0]), "+f"(d[1]), "+f"(d[2]), "+f"(d[3]), "+f"(d[4]), "+f"(d[5]), "+f"(d[6]), "+f"(d[7]), "+f"(d[8]), "+f"(d[9]), "+f"(d[10]), "+f"(d[11]), "+f"(d[12]), "+f"(d[13]), "+f"(d[14]), "+f"(d[15]), "+f"(d[16]), "+f"(d[17]), "+f"(d[18]), "+f"(d[19]), "+f"(d[20]), "+f"(d[21]), "+f"(d[22]), "+f"(d[23]), "+f"(d[24]), "+f"(d[25]), "+f"(d[26]), "+f"(d[27]), "+f"(d[28]), "+f"(d[29]), "+f"(d[30]), "+f"(d[31])
    : "r"(aoff), "n"((uint32_t)AD), "n"((uint32_t)(AD >> 32)), "n"(BD));
}
template<int SD, uint64_t AD, uint64_t BD, int SZ> __device__ __forceinline__ void wg_ss64h(float (&d)[SZ], uint32_t aoff) {
  if constexpr (SD == 0)
  asm volatile("{\n.reg .pred p;\n.reg .b64 ad, bd;\n.reg .b32 lo;\nsetp.ne.b32 p, 0, 0;\n"
    "add.u32 lo, %32, %33;\nmov.b64 ad, {lo, %34};\n"
    "mov.b64 bd, %35;\n"
    "wgmma.mma_async.sync.aligned.m64n64k16.f32.bf16.bf16 "
    "{%0, %1, %2, %3, %4, %5, %6, %7, %8, %9, %10, %11, %12, %13, %14, %15, %16, %17, %18, %19, %20, %21, %22, %23, %24, %25, %26, %27, %28, %29, %30, %31}, "
    "ad, bd, p, 1, 1, 0, 1;\n}\n"
    : "=f"(d[32]), "=f"(d[33]), "=f"(d[34]), "=f"(d[35]), "=f"(d[36]), "=f"(d[37]), "=f"(d[38]), "=f"(d[39]), "=f"(d[40]), "=f"(d[41]), "=f"(d[42]), "=f"(d[43]), "=f"(d[44]), "=f"(d[45]), "=f"(d[46]), "=f"(d[47]), "=f"(d[48]), "=f"(d[49]), "=f"(d[50]), "=f"(d[51]), "=f"(d[52]), "=f"(d[53]), "=f"(d[54]), "=f"(d[55]), "=f"(d[56]), "=f"(d[57]), "=f"(d[58]), "=f"(d[59]), "=f"(d[60]), "=f"(d[61]), "=f"(d[62]), "=f"(d[63])
    : "r"(aoff), "n"((uint32_t)AD), "n"((uint32_t)(AD >> 32)), "n"(BD));
  if constexpr (SD == 1)
  asm volatile("{\n.reg .pred p;\n.reg .b64 ad, bd;\n.reg .b32 lo;\nsetp.ne.b32 p, 1, 0;\n"
    "add.u32 lo, %32, %33;\nmov.b64 ad, {lo, %34};\n"
    "mov.b64 bd, %35;\n"
    "wgmma.mma_async.sync.aligned.m64n64k16.f32.bf16.bf16 "
    "{%0, %1, %2, %3, %4, %5, %6, %7, %8, %9, %10, %11, %12, %13, %14, %15, %16, %17, %18, %19, %20, %21, %22, %23, %24, %25, %26, %27, %28, %29, %30, %31}, "
    "ad, bd, p, 1, 1, 0, 1;\n}\n"
    : "+f"(d[32]), "+f"(d[33]), "+f"(d[34]), "+f"(d[35]), "+f"(d[36]), "+f"(d[37]), "+f"(d[38]), "+f"(d[39]), "+f"(d[40]), "+f"(d[41]), "+f"(d[42]), "+f"(d[43]), "+f"(d[44]), "+f"(d[45]), "+f"(d[46]), "+f"(d[47]), "+f"(d[48]), "+f"(d[49]), "+f"(d[50]), "+f"(d[51]), "+f"(d[52]), "+f"(d[53]), "+f"(d[54]), "+f"(d[55]), "+f"(d[56]), "+f"(d[57]), "+f"(d[58]), "+f"(d[59]), "+f"(d[60]), "+f"(d[61]), "+f"(d[62]), "+f"(d[63])
    : "r"(aoff), "n"((uint32_t)AD), "n"((uint32_t)(AD >> 32)), "n"(BD));
}

constexpr uint64_t dB128 = make_desc(SB, 8192, 1024, 1);
constexpr uint64_t dB128h = make_desc(SB, 4096, 1024, 1);
constexpr uint64_t dB64 = make_desc(SB, 4096, 512, 2);
constexpr uint64_t dA = make_desc(SB + OFF_X, 16, 1024, 1);
template<int I> struct IC { static constexpr int value = I; };
template<int B, int E, class F> __device__ __forceinline__ void sfor(F&& f) { if constexpr (B < E) { f(IC<B>{}); sfor<B + 1, E>(f); } }
#define SFOR(VAR, B, E) sfor<B, E>([&](auto VAR##_) __attribute__((always_inline)) { constexpr int VAR = decltype(VAR##_)::value;
#define SEND });

struct RowC { float c0, c1, c2; };

template<int LO, int HI, int NPR, int HOFF>
__device__ __forceinline__ void geglu_slice(uint32_t (&hp)[56], float (&acc)[64], const RowC& a, const RowC& b) {
  #pragma unroll
  for (int i = LO; i < HI; i++) {
    const RowC& c = (i & 1) ? b : a;
    hp[HOFF + i] = pack2(geglu1(acc[2 * i], acc[2 * NPR + 2 * i], c.c0, c.c1, c.c2), geglu1(acc[2 * i + 1], acc[2 * NPR + 2 * i + 1], c.c0, c.c1, c.c2));
  }
}
__device__ __forceinline__ uint32_t mapa(uint32_t addr, uint32_t rank) { uint32_t r; asm("mapa.shared::cluster.u32 %0, %1, %2;" : "=r"(r) : "r"(addr), "r"(rank)); return r; }
__device__ __forceinline__ void peer_send(float (&acc)[64], uint32_t rbuf, uint32_t rbar) {
  #pragma unroll
  for (int jp = 0; jp < 4; jp++) {
    const int b = 32 + 8 * jp;
    asm volatile("st.async.weak.shared::cluster.mbarrier::complete_tx::bytes.v4.b32 [%0], {%1, %2, %3, %4}, [%5];"
      :: "r"(rbuf + jp * 512), "r"(pack2(acc[b], acc[b + 1])), "r"(pack2(acc[b + 2], acc[b + 3])), "r"(pack2(acc[b + 4], acc[b + 5])), "r"(pack2(acc[b + 6], acc[b + 7])), "r"(rbar) : "memory");
  }
}
template<bool ADD, bool LAST = false>
__device__ __forceinline__ void stage_out(float (&acc)[64], uint32_t lbuf, uint32_t stsm_base, uint32_t lhi, uint32_t l7, uint32_t bar) {
  uint32_t u[16];
  if constexpr (ADD) {
    #pragma unroll
    for (int jp = 0; jp < 4; jp++)
      asm volatile("ld.shared.v4.b32 {%0, %1, %2, %3}, [%4];" : "=r"(u[4 * jp]), "=r"(u[4 * jp + 1]), "=r"(u[4 * jp + 2]), "=r"(u[4 * jp + 3]) : "r"(lbuf + jp * 512) : "memory");
  }
  if constexpr (LAST) { wg_wait<0>(); fence_regs<0, 32>(acc); }
  #pragma unroll
  for (int i = 0; i < 16; i++) { const uint32_t v = pack2(acc[2 * i], acc[2 * i + 1]); u[i] = ADD ? hadd2(v, u[i]) : v; }
  __syncwarp();
  #pragma unroll
  for (int jj = 0; jj < 4; jj++) stsm4(stsm_base + (((2 * jj + lhi) ^ l7) << 4), u[4 * jj], u[4 * jj + 1], u[4 * jj + 2], u[4 * jj + 3]);
  warp_arrive(bar);
}
__device__ __forceinline__ void poll_cnt(const unsigned* cnt, unsigned base, unsigned n) {
  asm volatile("{\n.reg .pred p;\n.reg .u32 c, v;\nmov.u32 c, 0;\nKV_LOOP:\n"
    "ld.relaxed.gpu.global.u32 v, [%0];\nsub.u32 v, v, %1;\nsetp.ge.u32 p, v, %2;\n@p bra KV_DONE;\n"
    "nanosleep.u32 40;\nadd.u32 c, c, 1;\nsetp.lt.u32 p, c, 2000000;\n@p bra KV_LOOP;\ntrap;\nKV_DONE:\n}\n" :: "l"(cnt), "r"(base), "r"(n) : "memory");
}

__global__ void __cluster_dims__(2, 1, 1) __launch_bounds__(384, 1)
fused_kernel(const __grid_constant__ Maps maps, const __nv_bfloat16* __restrict__ x, __nv_bfloat16* __restrict__ out) {
  extern __shared__ __align__(1024) char smraw[];
  const uint32_t sb = smem_u32(smraw);
  const int tid = threadIdx.x;
  const int mt = blockIdx.x >> 3, s = blockIdx.x & 7;
  STAMP(0);
  const uint32_t rank = s & 1;
  uint32_t budget = 0;
  const int w12 = __shfl_sync(0xffffffffu, tid >> 5, 0), wg = w12 >> 2;
  const int qc = 56 * s - 8 * (int)rank;
  if (wg == 2) {
    asm volatile("setmaxnreg.dec.sync.aligned.u32 40;");
    const int warp = w12 - 8;
    STAMPW(40 + warp);
    if (warp != 0 && elect_one()) {
      if (warp == 1) {
        mbar_init(sb + BAR_XW, 8); mbar_init(sb + BAR_XW2, 8); mbar_init(sb + BAR_TW, 8);
        mbar_init(sb + BAR_KVP, 256); mbar_init(sb + BAR_RDY2, 2);
        #pragma unroll
        for (int i = 0; i < 8; i++) { mbar_init(sb + BAR_RDY + 8 * i, 1); mbar_init(sb + BAR_OW + 8 * i, 4); }
      } else {
        #pragma unroll
        for (int i = 0; i < 16; i++) mbar_init(sb + BAR_DAT + 8 * ((warp - 2) * 16 + i), 1);
      }
      asm volatile("fence.mbarrier_init.release.cluster;" ::: "memory");
    }
    __syncwarp();
    STAMPW(44 + warp);
    asm volatile("barrier.cluster.arrive.relaxed.aligned;" ::: "memory");
    asm volatile("bar.sync 5, 384;" ::: "memory");
    if (warp == 0) {
      STAMPW(48);
      {
        const int lane = lane_id(), t = lane + 34;
        mbar_expect_tx(sb + BAR_DAT + 8 * lane, 2048);
        mbar_expect_tx(sb + BAR_FULL + 8 * (lane + 2), lane >= 19 && lane < 26 ? 16384 - 1024 * rank : 16384);
        if (t < 39) mbar_expect_tx(sb + BAR_FULL + 8 * t, t == 34 ? 16384 : (t == 35 ? 57344 : (t == 36 ? 53248 : 73728)));
        __syncwarp();
      }
      if (!elect_one()) return;
      #define FREED(T) asm volatile("barrier.sync %0, 96;" :: "n"(8 + ((T) & 7)) : "memory")
      const int ck = 64 * rank, cs = 64 * (rank ^ 1);
      const int f32 = 224 * s + 192 * (rank ^ 1), f64 = 224 * s + 32 * rank;
      #pragma unroll 1
      for (int i = 1; i < 12; i++) prefetch_map(&maps.x + i);
      mbar_wait(sb + BAR_X + 8 * (PFK - 2));
      asm volatile("cp.async.bulk.prefetch.L2.global [%0], %1;" :: "l"(maps.w[2] + blockIdx.x * 9408), "r"(9408) : "memory");
      mbar_wait(sb + BAR_X + 8 * XWAIT);
      #pragma unroll 1
      for (int t = 2; t < 7; t++) {
        const uint32_t fb = sb + BAR_FULL + 8 * t, dst = sb + OFF_SLOT + (t == 5 ? 2 : (t == 2 ? 1 : t)) * 16384;
        STAMPW(64 + t);
        tma2d(dst, &maps.qkv, fb, 448 + qc, t * 64);
        tma2d(dst + 8192, &maps.qkv, fb, 896 + qc, t * 64);
      }
      SFOR(t, 7, 35)
        constexpr int kr = (t % 7) * 64;
        const uint32_t fb = sb + BAR_FULL + 8 * t, dst = sb + buf_off(t);
        if constexpr (t == 20) asm volatile("barrier.sync 1, 96;" ::: "memory");
        else FREED(t < 12 ? t - 7 : (t < 20 ? t - 5 : t - 6));
        STAMPW(64 + t);
        if constexpr (t >= 21 && t < 28) {
          tma2d(dst, &maps.g32, fb, f32, kr);
          tma2d(dst + 4096, &maps.u32, fb, f32, kr);
          tma2d(dst + 8192, &maps.q32, fb, 56 * s + 24 * rank, kr);
          tma2d(dst + 12288, &maps.q32 + rank, fb, 56 * s + 32 * (rank ^ 1), kr);
        } else if constexpr (t < 7 + NG) {
          tma2d(dst, &maps.qkv, fb, 448 + qc, kr);
          tma2d(dst + 8192, &maps.qkv, fb, 896 + qc, kr);
        } else {
          tma2d(dst, &maps.g, fb, f64 + (t < 14 ? 0 : (t < 21 ? 64 : 128)), kr);
          tma2d(dst + 8192, &maps.u, fb, f64 + (t < 14 ? 0 : (t < 21 ? 64 : 128)), kr);
        }
      SEND
      SFOR(i, 0, 18)
        constexpr int t = ord_of(i);
        if constexpr (dep_of(i) != 0) FREED(dep_of(i));
        const uint32_t fb = sb + BAR_FULL + 8 * (t < 39 ? 35 : (t < 43 ? 36 : (t < 48 ? 37 : 38))), dst = sb + buf_off(t);
        STAMPW(64 + t);
        constexpr bool dir = t >= 40 && t < 43;
        constexpr int v = t < 40 ? t - 35 : t - 38, p = v >= 10 ? 2 : (v >= 5), st = dir ? 2 * (t - 40) : v - 5 * p;
        constexpr int sb2 = dir ? st + 1 : st;
        const int r0 = st == 0 ? 56 * s : (st == 1 ? f32 : f64 + 64 * (st - 2)), r1 = sb2 == 0 ? 56 * s : (sb2 == 1 ? f32 : f64 + 64 * (sb2 - 2));
        tma2d(dst, &maps.o - (st < 2 ? st : 2), fb, dir ? 384 : 128 * p + ck, r0);
        if constexpr (t != 42) tma2d(dst + (st == 1 ? 4096 : 8192), &maps.o - (sb2 < 2 ? sb2 : 2), fb, dir ? 384 : 128 * p + cs, r1);
      SEND
      STAMPW(1);
    } else {
      unsigned* cnt = &g_cnt[s * 32];
      unsigned* cnt2 = &g_cnt2[mt * 32];
      const int lane = lane_id();
      unsigned e = 0;
      if (lane == 0) { asm volatile("ld.relaxed.gpu.global.u32 %0, [%1];" : "=r"(e) : "l"(cnt) : "memory"); e >>= 4; }
      e = __shfl_sync(0xffffffffu, e, 0);
      const unsigned par = e & 1;
      asm volatile("barrier.cluster.wait.acquire.aligned;" ::: "memory");
      if (warp == 2) {
        mbar_wait(sb + BAR_FULL + 8 * 5);
        const uint4* src = (const uint4*)(x + (mt * 128 + s * 16) * DM) + lane;
        uint4* dst = (uint4*)(out + (mt * 128 + s * 16) * DM) + lane;
        #pragma unroll 1
        for (int b = 0; b < 4; b++) {
          uint4 v[7];
          #pragma unroll
          for (int i = 0; i < 7; i++) v[i] = __ldg(src + (b * 7 + i) * 32);
          #pragma unroll
          for (int i = 0; i < 7; i++) dst[(b * 7 + i) * 32] = v[i];
        }
        __syncwarp();
        if (lane == 0) asm volatile("red.release.gpu.global.add.u32 [%0], 1;" :: "l"(cnt2) : "memory");
      } else if (warp == 3) {
        mbar_wait(sb + BAR_XW); fence_async(); if (lane == 0) mbar_arrive(sb + BAR_XR);
        mbar_wait(sb + BAR_XW2); fence_async(); if (lane == 0) mbar_arrive(sb + BAR_XR2);
        mbar_wait(sb + BAR_TW); fence_async(); if (lane == 0) mbar_arrive(sb + BAR_TILES);
      } else if (mt == 0) {
        float4* z = (float4*)&g_kvsum[((par ^ 1u) * 8 + s) * KVN];
        #pragma unroll 1
        for (int i = 0; i < 21; i++) z[lane + 32 * i] = make_float4(0.f, 0.f, 0.f, 0.f);
      }
      const float* sum = &g_kvsum[(par * 8 + s) * KVN] + ((warp - 1) * 7 * 32 + lane) * 4;
      if (warp == 1 && lane == 0) asm volatile("st.shared.u32 [%0], %1;" :: "r"(sb + OFF_PAR), "r"(par) : "memory");
      if (warp == 1) {
        __syncwarp();
        if (lane == 0) mbar_arrive(sb + BAR_PAR);
        const uint32_t n = lane == 2 ? 9408 : (lane == 4 ? 3136 : 12544);
        const char* p = maps.w[lane < 5 ? lane : 0] + blockIdx.x * n;
        mbar_wait(sb + BAR_FULL + 8 * PFW);
        if (lane < (PFK ? 2 : 3)) asm volatile("cp.async.bulk.prefetch.L2.global [%0], %1;" :: "l"(p), "r"(n) : "memory");
        mbar_wait(sb + BAR_FULL + 8 * PFW2);
        if (lane == 3 || lane == 4) asm volatile("cp.async.bulk.prefetch.L2.global [%0], %1;" :: "l"(p), "r"(n) : "memory");
      }
      mbar_wait(sb + BAR_KVP);
      if (warp == 1) {
        STAMPW(2);
        if (lane == 0) asm volatile("red.release.gpu.global.add.u32 [%0], 1;" :: "l"(cnt) : "memory");
        STAMPW(3);
      } else {
        #pragma unroll
        for (int i = 0; i < 8; i++)
          asm volatile("st.shared.v4.u32 [%0], {%1, %1, %1, %1};" :: "r"(sb + OFF_KVB + ((warp - 2) * 256 + lane + 32 * i) * 16), "r"(0) : "memory");
      }
      asm volatile("bar.sync 3, 96;" ::: "memory");
      uint32_t bP = sb + OFF_KVB + (lane >> 2) * 144 + (lane & 3) * 4 + rank * 32 * 128, bM = bP - rank * 56 * 128;
      uint32_t bD = sb + OFF_KVB + (lane >> 3) * 2048 + (lane & 7) * 128 + ((7 ^ (lane & 7)) << 4) + rank * 32 * 128;
      asm volatile("" : "+r"(bP), "+r"(bM), "+r"(bD));
      if (lane == 0) poll_cnt(cnt, e << 4, 16);
      __syncwarp();
      if (warp == 1) STAMPW(4);
      float4 v[7];
      #pragma unroll
      for (int n = 0; n < 7; n++) {
        const float* p = sum + n * 128;
        asm volatile("ld.relaxed.gpu.global.v4.f32 {%0, %1, %2, %3}, [%4];" : "=f"(v[n].x), "=f"(v[n].y), "=f"(v[n].z), "=f"(v[n].w) : "l"(p) : "memory");
      }
      SFOR(w, 0, 3)
        if (warp == w + 1) {
          SFOR(n, 0, 7)
            constexpr int f = w * 7 + n, g = f >> 2, hb = g >= 2, j = f & 3, d = (g - hb) * 16;
            uint32_t a0 = ((d >= 24 ? bM : bP) ^ ((3 * hb + j) << 4)) + d * 128, a1 = ((d >= 16 ? bM : bP) ^ ((3 * hb + j) << 4)) + d * 128 + 1024;
            const bool cok = j == 3 * (1 - hb) ? (lane & 2) == 2 * hb : true;
            bool p0 = cok && g != 2, p1 = cok && (g == 1 ? lane < 16 : (g == 2 ? lane >= 16 : g != 4));
            if constexpr (f == 20) { a0 = bD + (lane >= 16 ? bM : bP) - bP; a1 = bD + 1024 + (lane >= 8 ? bM : bP) - bP; p0 = true; p1 = lane < 24; }
            asm volatile("{\n.reg .pred p, q;\nsetp.ne.u32 p, %4, 0;\nsetp.ne.u32 q, %5, 0;\n@p st.shared.u32 [%0], %2;\n@q st.shared.u32 [%1], %3;\n}"
              :: "r"(a0), "r"(a1), "r"(pack2(v[n].x, v[n].y)), "r"(pack2(v[n].z, v[n].w)), "r"((uint32_t)p0), "r"((uint32_t)p1) : "memory");
          SEND
        }
      SEND
      if (warp == 1) STAMPW(9);
      fence_async();
      __syncwarp();
      if (lane == 0) mbar_arrive(sb + BAR_KVB);
      if (warp == 1) STAMPW(5);
      if (warp < 3 && elect_one()) {
        poll_cnt(cnt2, e << 3, 8);
        asm volatile("fence.proxy.async;" ::: "memory");
        if (warp == 2) STAMPW(7);
        #pragma unroll 1
        for (int i = 0; i < NOUT; i++) {
          mbar_wait(sb + BAR_OW + (warp - 1) * 32 + i * 8);
          fence_async();
          const int p = (i + 3) & 3;
          asm volatile("cp.reduce.async.bulk.tensor.2d.global.shared::cta.add.tile.bulk_group [%0, {%2, %3}], [%1];"
            :: "l"(&maps.out), "r"(sb + OFF_X + (3 + p) * 16384 + (warp - 1) * 8192), "r"(128 * p + (i ? 64 * (int)rank : 0)), "r"(mt * 128 + (warp - 1) * 64) : "memory");
          if (warp == 2) STAMPW(20 + i);
        }
        asm volatile("cp.async.bulk.commit_group;" ::: "memory");
        asm volatile("cp.async.bulk.wait_group.read 0;" ::: "memory");
        if (warp == 2) STAMPW(12);
      }
    }
    return;
  }

  if (elect_one()) {
    if (w12 == 0) {
      #pragma unroll
      for (int i = 0; i < 7; i++) mbar_init(sb + BAR_X + 8 * i, 1);
      fence_async();
      STAMP(14);
      #pragma unroll
      for (int i = 0; i < 7; i++) { mbar_expect_tx(sb + BAR_X + 8 * i, 16384); tma2d(sb + OFF_X + i * 16384, &maps.x, sb + BAR_X + 8 * i, i * 64, mt * 128); }
      mbar_init(sb + BAR_FULL, 1); mbar_init(sb + BAR_FULL + 8, 1);
      fence_async();
      #pragma unroll
      for (int t = 0; t < 2; t++) {
        mbar_expect_tx(sb + BAR_FULL + 8 * t, 16384);
        const int f64 = 224 * s + 32 * rank;
        tma2d(sb + buf_off(t), t < NG ? &maps.g : &maps.qkv, sb + BAR_FULL + 8 * t, t < NG ? f64 : 448 + qc, t * 64);
        tma2d(sb + buf_off(t) + 8192, t < NG ? &maps.u : &maps.qkv, sb + BAR_FULL + 8 * t, t < NG ? f64 : 896 + qc, t * 64);
      }
      STAMP(15);
    } else {
      if ((sb & 0xFFFFFFu) != SB) __trap();
      #pragma unroll
      for (int i = 0; i < 6; i++) {
        const int n = i == 0 ? (w12 == 6 ? 4 : 1) : (i == 1 ? (w12 == 2 ? 5 : 1 + (w12 == 3)) : (i == 4 ? 1 + (w12 == 2) : (i == 5 ? 1 + (w12 <= 2) : 1)));
        mbar_init(sb + BAR_FULL + 8 * (w12 * 6 - 4 + i), n);
      }
      fence_async();
    }
  }
  __syncwarp();
  STAMP(40);
  asm volatile("barrier.cluster.arrive.relaxed.aligned;" ::: "memory");
  asm volatile("bar.sync 5, 384;" ::: "memory");
  STAMP(41);
  asm volatile("setmaxnreg.inc.sync.aligned.u32 232;");
  STAMP(42);
  const int lane = lane_id(), wl = w12 & 3, w8 = w12;
  const uint32_t is0 = (tid & 127) == 0;
  const uint32_t fb = sb + BAR_FULL;
  const uint32_t aoff = wg * 512;
  const uint32_t lrow = (lane & 7) + ((lane >> 3) & 1) * 8, lhi = lane >> 4, l7 = lane & 7;

  #define REL(T) do { if constexpr ((T) == 5 || (T) == 6) mbar_arrive_pred(sb + BAR_E56, is0); \
    else asm volatile("{\n.reg .pred p;\nsetp.eq.u32 p, %0, 0;\n@p bar.arrive %1, 96;\n}" :: "r"(wl), "n"(8 + ((T) & 7)) : "memory"); } while (0)
  float accA[64], accB[64];
  uint32_t hp[56];
  RowC ca, cb;
  float ra, rb, rla, rlb;
  uint32_t xr[112];
  float vA, vB, kvacc[20];
  uint32_t par;
  #define SQ_ACC(B0, B1) \
    _Pragma("unroll") \
    for (int b2 = B0; b2 < B1; b2++) { \
      uint32_t qa = 0, qb = 0; \
      _Pragma("unroll") \
      for (int i = 16 * b2; i < 16 * b2 + 16; i += 2) { qa = hfma2(xr[i], xr[i], qa); qb = hfma2(xr[i + 1], xr[i + 1], qb); } \
      vA += bf_lo(qa) + bf_hi(qa); vB += bf_lo(qb) + bf_hi(qb); \
    } \
    asm volatile("" : "+f"(vA), "+f"(vB) :: "memory");
  {
    float s0[4] = {0.f, 0.f, 0.f, 0.f}, s1[4] = {0.f, 0.f, 0.f, 0.f}, vs[4] = {0.f, 0.f, 0.f, 0.f};
    float tA, tB;
    uint32_t xrow = sb + OFF_X + (w8 * 16 + lrow) * 128 + ((lhi ^ l7) << 4);
    asm volatile("" : "+r"(xrow));
    #pragma unroll
    for (int kb = 0; kb < 7; kb++) {
      mbar_wait(sb + BAR_X + 8 * kb);
      STAMP(32 + kb);
      #pragma unroll
      for (int kk = 0; kk < 4; kk++) {
        const int i = (kb * 4 + kk) * 4;
        ldsm4(xr[i], xr[i + 1], xr[i + 2], xr[i + 3], (xrow ^ (kk << 5)) + kb * 16384);
      }
      #pragma unroll
      for (int kk = kb ? 0 : 4; kk < (kb == 6 ? 8 : 4); kk++) {
        const int i = (kb * 4 - 4 + kk) * 4;
        if (kb == NP + 1 && kk == 0) { tA = s0[0] + s1[0]; tB = s0[2] + s1[2]; }
        if (kk & 1) mma_rowsum(s1, xr[i], xr[i + 1], xr[i + 2], xr[i + 3]); else mma_rowsum(s0, xr[i], xr[i + 1], xr[i + 2], xr[i + 3]);
      }
      if (kb >= 1 && kb <= NP) {
        #pragma unroll
        for (int i = 0; i < 16; i++) {
          const float lo = bf_lo(xr[16 * kb - 16 + i]), hi = bf_hi(xr[16 * kb - 16 + i]);
          vs[i & 1] = fmaf(lo, lo, vs[i & 1]); vs[2 + (i & 1)] = fmaf(hi, hi, vs[2 + (i & 1)]);
        }
        asm volatile("" : "+f"(vs[0]), "+f"(vs[1]), "+f"(vs[2]), "+f"(vs[3]) :: "memory");
      }
    }
    STAMP(1);
    const float sA = s0[0] + s1[0], sB = s0[2] + s1[2];
    const float meanA = sA * (1.0f / DM), meanB = sB * (1.0f / DM);
    uint32_t mA = pack2(meanA, meanA), mB = pack2(meanB, meanB);
    #pragma unroll
    for (int i = 0; i < 16; i++) xr[i] = hsub2(xr[i], (i & 1) ? mB : mA);
    SFOR(kb, 0, 7)
      budget = 0;
      mbar_wait(fb + 8 * kb);
      STAMP(64 + kb);
      wg_fence();
      SFOR(kk, 0, 4)
        constexpr int i = (kb * 4 + kk) * 4;
        if constexpr (kb < NG) wg_rs128<(kb | kk) != 0, dB128 + ((buf_off(kb) + kk * 2048) >> 4)>(accB, xr[i], xr[i + 1], xr[i + 2], xr[i + 3]);
        else wg_rs120<(kb != NG || kk != 0), dB128 + ((buf_off(kb) + kk * 2048) >> 4)>(accA, xr[i], xr[i + 1], xr[i + 2], xr[i + 3], rank);
      SEND
      wg_commit();
      #pragma unroll
      for (int kk = 0; kk < 4; kk++) {
        const int i = (kb * 4 + kk) * 4;
        stsm4((xrow ^ (kk << 5)) + kb * 16384, xr[i], xr[i + 1], xr[i + 2], xr[i + 3]);
      }
      if constexpr (kb == 4) warp_arrive(sb + BAR_XW);
      if constexpr (kb == 6) warp_arrive(sb + BAR_XW2);
      if constexpr (kb > 0) { wg_wait<1>(); REL(kb - 1); }
      if constexpr (kb + 1 >= NP && kb < 5) pin2(mA, mB);
      if constexpr (kb < 6) {
        #pragma unroll
        for (int i = 16 * (kb + 1); i < 16 * (kb + 2); i++) xr[i] = hsub2(xr[i], (i & 1) ? mB : mA);
      }
      if constexpr (kb == 0) {
        const float eA = meanA - bf_lo(mA), eB = meanB - bf_lo(mB);
        vA = vs[0] + vs[2] + 0.25f * (meanA * (64.f * NP * meanA - 2.f * tA) + eA * ((448.f - 64.f * NP) * (meanA + bf_lo(mA)) - 2.f * (sA - tA)));
        vB = vs[1] + vs[3] + 0.25f * (meanB * (64.f * NP * meanB - 2.f * tB) + eB * ((448.f - 64.f * NP) * (meanB + bf_lo(mB)) - 2.f * (sB - tB)));
        asm volatile("" : "+f"(vA), "+f"(vB) :: "memory");
      }
      if constexpr (kb + 1 >= NP && kb < 5) { SQ_ACC(kb + 1, kb + 2) }
      if constexpr (kb == 6) { SQ_ACC(6, 7) }
    SEND
  }
  STAMP(2);
  #define SS_ISSUE(ACC, T) \
    SFOR(kk, 0, 4) \
      wg_ss128<(kb | kk) != 0, dA + ((kb * 16384 + kk * 32) >> 4), dB128 + ((buf_off(T) + kk * 2048) >> 4)>(ACC, aoff); \
    SEND
  {
    const uint32_t lane1 = lane_id(), trow = sb + OFF_SLOT + (2 + 4 * wg) * 16384 + (wl * 16 + (lane1 & 15)) * 128 + (((lane1 >> 4) ^ (lane1 & 7)) << 4);
    uint32_t pk[14], vv[14];
    #define PHI_K(LO, HI) _Pragma("unroll") \
      for (int i = LO; i < HI; i++) pk[i] = (i & 1) ? phi2(accA[2 * i], accA[2 * i + 1], rb, rlb) : phi2(accA[2 * i], accA[2 * i + 1], ra, rla);
    #define SCALE_V(LO, HI) _Pragma("unroll") \
      for (int i = LO; i < HI; i++) { const float r = (i & 1) ? rb : ra; vv[i] = pack2(accA[32 + 2 * i] * r, accA[33 + 2 * i] * r); }
    #define ST_K(J) stsm4(trow ^ ((J) << 5), pk[4 * (J)], pk[4 * (J) + 1], pk[4 * (J) + 2], pk[4 * (J) + 3]);
    #define ST_V(J) stsm4((trow ^ ((J) << 5)) + 8192, vv[4 * (J)], vv[4 * (J) + 1], vv[4 * (J) + 2], vv[4 * (J) + 3]);
    SFOR(kb, 0, 7)
      constexpr int t = 7 + kb;
      mbar_wait(fb + 8 * t);
      STAMP(64 + t);
      wg_fence();
      if constexpr (kb < NG) {
        SFOR(kk, 0, 4)
          wg_ss120b<1, dA + ((kb * 16384 + kk * 32) >> 4), dB128 + ((buf_off(t) + kk * 2048) >> 4)>(accA, aoff, rank);
        SEND
      } else {
        SS_ISSUE(accB, t)
      }
      wg_commit();
      if constexpr (kb == 4) {
        PHI_K(4, 8) SCALE_V(2, 4) ST_K(1) ST_V(0)
      } else if constexpr (kb == 5) {
        PHI_K(8, 12) SCALE_V(4, 8) ST_K(2) ST_V(1)
      } else if constexpr (kb == 6) {
        asm volatile("ld.shared.u32 %0, [%1];" : "=r"(par) : "r"(sb + OFF_PAR) : "memory");
        PHI_K(12, 14) SCALE_V(8, 14) ST_V(2)
        const uint32_t one = (lane1 & 3) == 0 ? 0x00003F80u : 0u;
        stsm4((trow ^ 96) + 8192, vv[12], vv[13], one, one);
        stsm4(trow ^ 96, pk[12], pk[13], 0u, 0u);
        warp_arrive(sb + BAR_TW);
      }
      wg_wait<1>();
      if constexpr (kb == 2) fence_regs<0, 60>(accA);
      REL(t - 1);
      if constexpr (kb == 0) {
        vA += __shfl_xor_sync(0xffffffffu, vA, 1); vB += __shfl_xor_sync(0xffffffffu, vB, 1);
        vA += __shfl_xor_sync(0xffffffffu, vA, 2); vB += __shfl_xor_sync(0xffffffffu, vB, 2);
        vA = fmaxf(vA * (1.0f / DM), 0.f); vB = fmaxf(vB * (1.0f / DM), 0.f);
        ra = rcp(bf_round(sqrt_approx(bf_round(bf_round(vA) + 1e-5f))));
        rb = rcp(bf_round(sqrt_approx(bf_round(bf_round(vB) + 1e-5f))));
        ca.c0 = 0.7978845608f * ra; ca.c1 = 0.0356774081f * ra * ra * ra; ca.c2 = 0.5f * ra * ra;
        cb.c0 = 0.7978845608f * rb; cb.c1 = 0.0356774081f * rb * rb * rb; cb.c2 = 0.5f * rb * rb;
        rla = ra * 1.4426950409f; rlb = rb * 1.4426950409f;
        asm volatile("" : "+f"(ra), "+f"(rb), "+f"(rla), "+f"(rlb), "+f"(ca.c0), "+f"(ca.c1), "+f"(ca.c2), "+f"(cb.c0), "+f"(cb.c1), "+f"(cb.c2) :: "memory");
      } else if constexpr (kb == 2) {
        PHI_K(0, 4) SCALE_V(0, 2) ST_K(0)
        asm volatile("" : "+r"(vv[0]), "+r"(vv[1]) :: "memory");
      }
    SEND
  }
  STAMP(3);
  #define EPI16(ACC, HOFF) \
    if constexpr (kb == 0) geglu_slice<0, 3, 16, HOFF>(hp, ACC, ca, cb); \
    else if constexpr (kb >= 2 && kb < 5) geglu_slice<3 * kb - 3, 3 * kb, 16, HOFF>(hp, ACC, ca, cb); \
    else if constexpr (kb >= 5) geglu_slice<2 * kb + 2, 2 * kb + 4, 16, HOFF>(hp, ACC, ca, cb);
  SFOR(kb, 0, 7)
    constexpr int t = 14 + kb;
    mbar_wait(fb + 8 * t);
    STAMP(64 + t);
    wg_fence();
    if constexpr (kb == 1) {
      SFOR(kk, 0, 8)
        constexpr uint64_t da = dB128 + ((OFF_SLOT + 2 * 16384) >> 4) + (kk >> 2) * 4096 + (kk & 3) * 128;
        wg_ss40t<kk != 0, da, da + 512>(kvacc, wg * 3);
      SEND
      wg_commit();
      wg_wait<1>();
      REL(14);
      wg_fence();
    }
    SS_ISSUE(accA, t)
    wg_commit();
    wg_wait<1>();
    if constexpr (kb == 1) {
      asm volatile("{\n.reg .pred p;\nsetp.eq.u32 p, %0, 0;\n@p bar.arrive 1, 96;\n}" :: "r"(wl) : "memory");
      fence_regs<0, 20>(kvacc);
      const int lane = lane_id(), q = lane & 3;
      float* sum = &g_kvsum[(par * 8 + s) * KVN];
      const uint32_t okw = wg == 0 ? (wl < 2) : (wl * 32 + lane >= 48), oke = okw && (q >> 1) == wg;
      const bool hb0 = wl >= 2, hb1 = wl * 16 + (lane >> 2) >= 20;
      float* p = sum + ((wg == 0 ? wl * 4 : 4 + wl * 4) * 32 + lane) * 4;
      #pragma unroll
      for (int j = 0; j < 4; j++)
        asm volatile("{\n.reg .pred p;\nsetp.ne.u32 p, %5, 0;\n@p red.relaxed.gpu.global.add.v4.f32 [%0], {%1, %2, %3, %4};\n}"
          :: "l"(p + j * 128), "f"(kvacc[4 * j]), "f"(kvacc[4 * j + 1]), "f"(kvacc[4 * j + 2]), "f"(kvacc[4 * j + 3]),
             "r"(j == 0 ? (wg ? oke : okw) : (j == 3 ? (wg ? okw : oke) : okw)) : "memory");
      asm volatile("{\n.reg .pred p;\nsetp.ne.u32 p, %5, 0;\n@p red.relaxed.gpu.global.add.v4.f32 [%0], {%1, %2, %3, %4};\n}"
        :: "l"(sum + (20 * 32 + wl * 8 + (lane >> 2)) * 4), "f"(hb0 ? 0.f : kvacc[16]), "f"(hb0 ? kvacc[16] : 0.f), "f"(hb1 ? 0.f : kvacc[18]), "f"(hb1 ? kvacc[18] : 0.f), "r"((uint32_t)(wg == 1 && q == 0)) : "memory");
      mbar_arrive(sb + BAR_KVP);
    } else {
      if constexpr (kb == 0) fence_regs<0, 64>(accB);
      REL(t - 1);
      geglu_slice<kb == 0 ? 0 : (kb == 2 ? 3 : 3 * kb - 5), kb == 0 ? 3 : 3 * kb - 2, 16, 8>(hp, accB, ca, cb);
    }
  SEND
  STAMP(4);
  SFOR(kb, 0, 7)
    constexpr int t = 21 + kb;
    mbar_wait(fb + 8 * t);
    STAMP(64 + t);
    wg_fence();
    SFOR(kk, 0, 4)
      wg_ss120<(kb | kk) != 0, dA + ((kb * 16384 + kk * 32) >> 4), dB64 + ((buf_off(t) + kk * 1024) >> 4)>(accB, aoff);
    SEND
    wg_commit();
    wg_wait<1>();
    if constexpr (kb == 0) fence_regs<0, 64>(accA);
    REL(t - 1);
    EPI16(accA, 24)
  SEND
  STAMP(5);
  uint32_t op[14];
  {
    uint32_t pq[14];
    SFOR(kb, 0, 7)
      constexpr int t = 28 + kb;
      mbar_wait(fb + 8 * t);
      if constexpr (kb == 6) asm volatile("{\n.reg .pred p;\nsetp.eq.u32 p, %0, 0;\n@p bar.sync 6, 256;\n}" :: "r"(wg) : "memory");
      STAMP(64 + t);
      wg_fence();
      SS_ISSUE(accA, t)
      if constexpr (kb == 4) {
        SFOR(kk, 0, 3)
          wg_rs64h<kk != 0, dB128 + ((OFF_KVB + kk * 2048) >> 4)>(accB, pq[4 * kk], pq[4 * kk + 1], pq[4 * kk + 2], pq[4 * kk + 3]);
        SEND
        wg_rs64h<1, dB128 + ((OFF_KVB + 6144) >> 4)>(accB, pq[12], pq[13], 0u, 0u);
      }
      wg_commit();
      if constexpr (kb == 6) asm volatile("{\n.reg .pred p;\nsetp.ne.u32 p, %0, 0;\n@p bar.arrive 6, 256;\n}" :: "r"(wg) : "memory");
      wg_wait<1>();
      if constexpr (kb == 0) fence_regs<0, 60>(accB);
      REL(t - 1);
      constexpr int plo = kb == 0 ? 0 : 5 * kb - 5, phi_ = kb == 0 ? 5 : (kb == 1 ? 0 : 5 * kb);
      #pragma unroll
      for (int i = plo; i < phi_ && i < 14; i++)
        pq[i] = (i & 1) ? phi2(accB[32 + 2 * i], accB[33 + 2 * i], rb, rlb) : phi2(accB[32 + 2 * i], accB[33 + 2 * i], ra, rla);
      if constexpr (kb >= 3 && kb < 6) geglu_slice<kb == 3 ? 0 : 4 * kb - 15, kb == 5 ? 8 : 4 * kb - 11, 8, 0>(hp, accB, ca, cb);
      if constexpr (kb == 5) {
        fence_regs<32, 64>(accB);
        const int lane = lane_id(), q = lane & 3;
        float dn[4];
        #pragma unroll
        for (int i = 0; i < 4; i++) dn[i] = rcp(__shfl_sync(0xffffffffu, accB[60 + i], lane & ~3) + 1e-6f);
        #pragma unroll
        for (int i = 0; i < 14; i++) {
          const int j = i >> 1, hf = i & 1;
          const float dv = j < 3 ? dn[2 * hf] : (j > 3 ? dn[2 * hf + 1] : (q < 2 ? dn[2 * hf] : dn[2 * hf + 1]));
          op[i] = pack2(accB[32 + 2 * i] * dv, accB[33 + 2 * i] * dv);
        }
      }
    SEND
  }
  STAMP(6);
  uint32_t xb = w8;
  asm volatile("" : "+r"(xb));
  xb = sb + OFF_X + 3 * 16384 + xb * 2048;
  const uint32_t lane2 = lane_id(), lrow2 = lane2 & 15, lhi2 = lane2 >> 4, l72 = lane2 & 7;
  const uint32_t peer_xb = mapa(xb + lane2 * 16, rank ^ 1), peer_bar = mapa(sb + BAR_DAT + w8 * 32, rank ^ 1);
  const uint32_t owb = sb + BAR_OW + wg * 32;
  #define PP_WAIT() asm volatile("bar.sync %0, 256;" :: "r"(6 + wg) : "memory")
  #define PP_PASS() asm volatile("bar.arrive %0, 256;" :: "r"(7 - wg) : "memory")
  #define FULL(T) mbar_wait(fb + 8 * (T))
  #define G2_AB(WG, ACC, T, O, OH) \
    WG<0, (dB128 + ((buf_off(T) + (O)) >> 4))>(ACC, op[0], op[1], op[2], op[3]); \
    WG<1, (dB128 + ((buf_off(T) + (O) + 2048) >> 4))>(ACC, op[4], op[5], op[6], op[7]); \
    WG<1, (dB128 + ((buf_off(T) + (O) + 4096) >> 4))>(ACC, op[8], op[9], op[10], op[11]); \
    WG<1, (dB128 + ((buf_off(T) + (O) + 6144) >> 4))>(ACC, op[12], op[13], 0u, 0u); \
    WG<1, (dB128h + ((OH) >> 4))>(ACC, hp[0], hp[1], hp[2], hp[3]); \
    WG<1, (dB128h + (((OH) + 2048) >> 4))>(ACC, hp[4], hp[5], hp[6], hp[7]);
  #define G2_H(WG, ACC, OFF, H0, K0, K1) \
    SFOR(kk, K0, K1) \
      WG<1, (dB128 + (((OFF) + kk * 2048) >> 4))>(ACC, hp[(H0) + 4 * kk], hp[(H0) + 4 * kk + 1], hp[(H0) + 4 * kk + 2], hp[(H0) + 4 * kk + 3]); \
    SEND
  #define XSEND(ACC, P) peer_send(ACC, peer_xb + (P) * 16384, peer_bar + (P) * 8)
  #define XRECV(ACC, P) mbar_wait(sb + BAR_DAT + w8 * 32 + (P) * 8); STAMP(26 + (P)); \
    stage_out<true, (P) == 2>(ACC, xb + (P) * 16384 + lane2 * 16, xb + (P) * 16384 + lrow2 * 128, lhi2, l72, owb + 8 + (P) * 8)
  #define PP_WAIT_IF(W) asm volatile("{\n.reg .pred p;\nsetp.eq.u32 p, %0, " #W ";\n@p bar.sync 6 + " #W ", 256;\n}" :: "r"(wg) : "memory")
  #define PP_PASS_IF(W) asm volatile("{\n.reg .pred p;\nsetp.eq.u32 p, %0, " #W ";\n@p bar.arrive 7 - " #W ", 256;\n}" :: "r"(wg) : "memory")
  #define BURST1(W) \
      FULL(35); \
      if (W == 1) PP_WAIT(); \
      STAMP(64 + 35); \
      wg_fence(); \
      G2_AB(wg_rs128, accB, 35, 0, buf_off(36)) \
      G2_H(wg_rs128, accB, buf_off(37), 8, 0, 4) \
      G2_H(wg_rs128, accB, buf_off(38), 24, 0, 3) \
      wg_commit(); \
      if (W == 0) PP_PASS(); \
      G2_H(wg_rs128, accB, buf_off(38), 24, 3, 4) \
      wg_commit(); \
      if (W == 1) FULL(36); \
      wg_wait<1>(); \
      STAMP(64 + 36); \
      REL(37);
  #define EPI4() \
      fence_regs<0, 64>(accA); \
      REL(34); \
      asm volatile("{\n.reg .pred p;\nelect.sync _|p, 0xffffffff;\n@p mbarrier.arrive.shared::cluster.b64 _, [%0];\n}" :: "r"(mapa(sb + BAR_RDY + w8 * 8, rank ^ 1)) : "memory"); \
      FULL(35); \
      geglu_slice<0, 16, 16, 40>(hp, accA, ca, cb); \
      STAMP(64 + 37);
  if (wg == 0) {
    BURST1(0)
    EPI4()
    FULL(36);
    PP_WAIT();
  } else {
    wg_wait<0>();
    EPI4()
    BURST1(1)
  }
  STAMP(64 + 38);
  wg_fence();
  G2_H(wg_rs128, accB, buf_off(39), 40, 0, 4)
  G2_AB(wg_rs64, accA, 40, 0, buf_off(40) + 8192)
  G2_H(wg_rs64, accA, buf_off(41), 8, 0, 8)
  G2_H(wg_rs64, accA, buf_off(42), 40, 0, 2)
  wg_commit();
  PP_PASS();
  G2_H(wg_rs64, accA, buf_off(42), 40, 2, 4)
  wg_commit();
  wg_wait<1>();
  fence_regs<0, 64>(accB);
  STAMP(64 + 39);
  REL(41);
  asm volatile("{\n.reg .pred p;\nsetp.ne.u32 p, %1, 0;\n@p mbarrier.arrive.shared::cluster.b64 _, [%0];\n}" :: "r"(mapa(sb + BAR_RDY2, rank ^ 1)), "r"(is0) : "memory");
  mbar_wait(sb + BAR_RDY + w8 * 8);
  XSEND(accB, 0);
  wg_wait<0>();
  fence_regs<0, 32>(accA);
  stage_out<false>(accA, 0, xb + 3 * 16384 + lrow2 * 128, lhi2, l72, owb);
  FULL(37);
  STAMP(64 + 40);
  PP_WAIT();
  STAMP(64 + 41);
  wg_fence();
  G2_AB(wg_rs128, accA, 43, 0, buf_off(44))
  G2_H(wg_rs128, accA, buf_off(45), 8, 0, 4)
  G2_H(wg_rs128, accA, buf_off(46), 24, 0, 4)
  G2_H(wg_rs128, accA, buf_off(47), 40, 0, 3)
  wg_commit();
  PP_PASS();
  G2_H(wg_rs128, accA, buf_off(47), 40, 3, 4)
  wg_commit();
  XRECV(accB, 0);
  mbar_wait(sb + BAR_RDY2);
  wg_wait<0>();
  fence_regs<0, 64>(accA);
  STAMP(64 + 42);
  XSEND(accA, 1);
  FULL(38);
  STAMP(64 + 43);
  PP_WAIT();
  STAMP(64 + 44);
  wg_fence();
  G2_AB(wg_rs64h, accB, 48, 8192, buf_off(49) + 4096)
  G2_H(wg_rs64h, accB, buf_off(50) + 8192, 8, 0, 4)
  G2_H(wg_rs64h, accB, buf_off(51) + 8192, 24, 0, 4)
  G2_H(wg_rs64h, accB, buf_off(52) + 8192, 40, 0, 2)
  wg_commit();
  PP_PASS();
  G2_H(wg_rs64h, accB, buf_off(52) + 8192, 40, 2, 4)
  wg_commit();
  XRECV(accA, 1);
  wg_wait<0>();
  fence_regs<32, 64>(accB);
  STAMP(64 + 45);
  XSEND(accB, 2);
  STAMP(64 + 46);
  PP_WAIT();
  STAMP(64 + 47);
  wg_fence();
  G2_AB(wg_rs64, accB, 48, 0, buf_off(49))
  G2_H(wg_rs64, accB, buf_off(50), 8, 0, 4)
  G2_H(wg_rs64, accB, buf_off(51), 24, 0, 4)
  G2_H(wg_rs64, accB, buf_off(52), 40, 0, 2)
  wg_commit();
  PP_PASS_IF(1);
  G2_H(wg_rs64, accB, buf_off(52), 40, 2, 4)
  wg_commit();
  XRECV(accB, 2);
  STAMP(12);
}

typedef CUresult (*PFN_enc)(CUtensorMap*, CUtensorMapDataType, cuuint32_t, void*, const cuuint64_t*, const cuuint64_t*, const cuuint32_t*, const cuuint32_t*,
                            CUtensorMapInterleave, CUtensorMapSwizzle, CUtensorMapL2promotion, CUtensorMapFloatOOBfill);
void enc2d(PFN_enc enc, CUtensorMap* m, const void* base, uint64_t inner, uint64_t outer, uint32_t bi, uint32_t bo, CUtensorMapSwizzle sw) {
  cuuint64_t dims[2] = {inner, outer}; cuuint64_t strides[1] = {inner * 2};
  cuuint32_t box[2] = {bi, bo}; cuuint32_t es[2] = {1, 1};
  enc(m, CU_TENSOR_MAP_DATA_TYPE_BFLOAT16, 2, const_cast<void*>(base), dims, strides, box, es, CU_TENSOR_MAP_INTERLEAVE_NONE, sw,
      CU_TENSOR_MAP_L2_PROMOTION_L2_128B, CU_TENSOR_MAP_FLOAT_OOB_FILL_NONE);
}

}

extern "C" void kernel_launch(void* const* d_in, const int* in_sizes, int n_in, void* d_out, int out_size) {
  static PFN_enc enc = nullptr;
  if (!enc) {
    void* fn = nullptr; cudaDriverEntryPointQueryResult qr;
    cudaGetDriverEntryPoint("cuTensorMapEncodeTiled", &fn, cudaEnableDefault, &qr);
    enc = (PFN_enc)fn;
    cudaFuncSetAttribute(fused_kernel, cudaFuncAttributeMaxDynamicSharedMemorySize, SMEM_BYTES);
  }
  Maps mp;
  const CUtensorMapSwizzle S128 = CU_TENSOR_MAP_SWIZZLE_128B, S64 = CU_TENSOR_MAP_SWIZZLE_64B;
  enc2d(enc, &mp.x, d_in[0], 448, 2048, 64, 128, S128);
  enc2d(enc, &mp.qkv, d_in[1], 1344, 448, 64, 64, S128);
  enc2d(enc, &mp.g, d_in[4], 1792, 448, 64, 64, S128);
  enc2d(enc, &mp.u, d_in[5], 1792, 448, 64, 64, S128);
  enc2d(enc, &mp.q32, d_in[1], 1344, 448, 32, 64, S64);
  enc2d(enc, &mp.q24, d_in[1], 1344, 448, 24, 64, S64);
  enc2d(enc, &mp.g32, d_in[4], 1792, 448, 32, 64, S64);
  enc2d(enc, &mp.u32, d_in[5], 1792, 448, 32, 64, S64);
  enc2d(enc, &mp.d, d_in[6], 448, 1792, 64, 64, S128);
  enc2d(enc, &mp.d32, d_in[6], 448, 1792, 64, 32, S128);
  enc2d(enc, &mp.o, d_in[2], 448, 448, 64, 64, S128);
  enc2d(enc, &mp.out, d_out, 448, 2048, 64, 64, S128);
  mp.w[0] = (const char*)d_in[4]; mp.w[1] = (const char*)d_in[5]; mp.w[2] = (const char*)d_in[1]; mp.w[3] = (const char*)d_in[6]; mp.w[4] = (const char*)d_in[2];
  fused_kernel<<<128, 384, SMEM_BYTES>>>(mp, (const __nv_bfloat16*)d_in[0], (__nv_bfloat16*)d_out);
}
```

```cpp
#include <cuda_runtime.h>
#include <cuda.h>
#include <cuda_bf16.h>
#include <stdint.h>

#define WDELAY 2
#define W0POS 6
#define PFM 2
#define NG 2
#define NP 3
#define PFW 4
#define PFW2 11
#define PFK 2
#define PFX 32
#define PFXB 0
#define T01 1
#define XISS 1
#define NL 2
#define PW1 (NL < 7 ? BAR_X + 8 * NL : BAR_FULL)
#define PW2 (NL < 7 ? BAR_X + 8 * (NL > XWAIT ? NL : XWAIT) : BAR_FULL + 8)
#define TFIRST 1
#define ES 1
#define MC 0
#define NL0 2
#define L2H ".L2::128B"
#define LASTRED 0
#define NOUT (LASTRED ? 3 : 4)
#define XWAIT 3
namespace {

constexpr int DM = 448;
constexpr uint32_t SB = 0x400;
constexpr uint32_t OFF_X = 0;
constexpr uint32_t OFF_SLOT = 7 * 16384;
constexpr uint32_t OFF_BAR = 14 * 16384;
constexpr uint32_t BAR_FULL = OFF_BAR;
constexpr uint32_t BAR_X = OFF_BAR + 1024;
constexpr uint32_t BAR_XW = OFF_BAR + 1080;
constexpr uint32_t BAR_XR = BAR_FULL + 8 * 7;
constexpr uint32_t BAR_TW = OFF_BAR + 1096;
constexpr uint32_t BAR_TILES = BAR_FULL + 8 * 15;
constexpr uint32_t BAR_KVP = OFF_BAR + 1112;
constexpr uint32_t BAR_KVB = BAR_FULL + 8 * 32;
constexpr uint32_t BAR_PAR = BAR_FULL + 8 * 13;
constexpr uint32_t BAR_E56 = BAR_FULL + 8 * 9;
constexpr uint32_t OFF_PAR = OFF_BAR + 1144;
constexpr uint32_t BAR_RDY = OFF_BAR + 1152;
constexpr uint32_t BAR_DAT = OFF_BAR + 1216;
constexpr uint32_t BAR_OW = OFF_BAR + 1472;
#define SMEM_BYTES (OFF_BAR + 1536 + TSB)
constexpr uint32_t OFF_KVB = OFF_SLOT + 6 * 16384 + 8192;
constexpr uint32_t BAR_XW2 = OFF_BAR + 1000, BAR_XR2 = BAR_FULL + 8 * 12;
constexpr uint32_t BAR_RDY2 = OFF_BAR + 1016;
constexpr int KVN = 21 * 128;

__device__ float g_kvsum[2 * 8 * KVN];
__device__ unsigned g_cnt[8 * 32];
__device__ unsigned g_cnt2[16 * 32];
#define STAMP(i)
#define STAMPW(i)
#define GSTAMP(v)
#define TSB 0

struct Maps { CUtensorMap x, qkv, q32, q24, g32, u32, g, u, d, d32, o, out; const char* w[5]; };

__host__ __device__ constexpr uint32_t buf_off(int t) {
  constexpr int t0[15] = {5, 0, 1, 3, 4, 2, 6, 5, 0, 1, 3, 4, 5, 0, 1};
  if (t < 15) return OFF_SLOT + t0[t] * 16384;
  if (t < 35) return OFF_SLOT + ((t - 12) % 6) * 16384;
  constexpr int tb[18] = {0, 26, 2, 24, 8, 10, 4, 27, 14, 22, 16, 18, 20, 0, 23, 2, 24, 4};
  return tb[t - 35] * 8192;
}
__host__ __device__ constexpr int ord_of(int i) { constexpr int tb[18] = {36, 35, 37, 38, 41, 39, 42, 40, 43, 45, 46, 47, 44, 49, 48, 50, 51, 52}; return tb[i]; }
__host__ __device__ constexpr int dep_of(int i) { constexpr int tb[18] = {0, 0, 29, 30, 31, 32, 0, 33, 0, 0, 0, 0, 34, 0, 37, 0, 41, 0}; return tb[i]; }

__device__ __forceinline__ uint32_t smem_u32(const void* p) { return (uint32_t)__cvta_generic_to_shared(p); }
__device__ __forceinline__ void mbar_init(uint32_t bar, uint32_t cnt) { asm volatile("mbarrier.init.shared::cta.b64 [%0], %1;" :: "r"(bar), "r"(cnt) : "memory"); }
__device__ __forceinline__ void mbar_expect_tx(uint32_t bar, uint32_t bytes) { asm volatile("mbarrier.arrive.expect_tx.shared::cta.b64 _, [%0], %1;" :: "r"(bar), "r"(bytes) : "memory"); }
__device__ __forceinline__ void mbar_arrive(uint32_t bar) { asm volatile("mbarrier.arrive.shared::cta.b64 _, [%0];" :: "r"(bar) : "memory"); }
__device__ __forceinline__ void mbar_arrive_pred(uint32_t bar, uint32_t pred) {
  asm volatile("{\n.reg .pred p;\nsetp.ne.u32 p, %1, 0;\n@p mbarrier.arrive.shared::cta.b64 _, [%0];\n}" :: "r"(bar), "r"(pred) : "memory");
}
__device__ __forceinline__ void mbar_wait_(uint32_t bar, uint32_t& budget) {
  asm volatile("{\n.reg .pred P1;\nLAB_WAIT:\n"
    "mbarrier.try_wait.parity.shared::cta.b64 P1, [%1], 0;\n"
    "add.u32 %0, %0, 1;\nsetp.lt.and.u32 P1, %0, 8000000, !P1;\n@P1 bra LAB_WAIT;\n}\n" : "+r"(budget) : "r"(bar) : "memory");
}
__device__ __forceinline__ void cp_wait(int n) {
  switch (n) {
    case 0: asm volatile("cp.async.wait_group 0;" ::: "memory"); break;
    case 1: asm volatile("cp.async.wait_group 1;" ::: "memory"); break;
    case 2: asm volatile("cp.async.wait_group 2;" ::: "memory"); break;
    case 3: asm volatile("cp.async.wait_group 3;" ::: "memory"); break;
    case 4: asm volatile("cp.async.wait_group 4;" ::: "memory"); break;
    case 5: asm volatile("cp.async.wait_group 5;" ::: "memory"); break;
    default: asm volatile("cp.async.wait_group 6;" ::: "memory"); break;
  }
}
#define mbar_wait(bar) mbar_wait_(bar, budget)
__device__ __forceinline__ void tma2d(uint32_t dst, const CUtensorMap* m, uint32_t bar, int c0, int c1) {
  asm volatile("cp.async.bulk.tensor.2d.shared::cluster.global.mbarrier::complete_tx::bytes [%0], [%1, {%3, %4}], [%2];"
    :: "r"(dst), "l"(m), "r"(bar), "r"(c0), "r"(c1) : "memory");
}
__device__ __forceinline__ uint32_t elect_one() {
  uint32_t p; asm volatile("{\n.reg .pred P;\nelect.sync _|P, 0xffffffff;\nselp.u32 %0, 1, 0, P;\n}" : "=r"(p)); return p;
}
__device__ __forceinline__ int lane_id() { int l; asm volatile("mov.u32 %0, %%laneid;" : "=r"(l)); return l; }
__device__ __forceinline__ void prefetch_map(const CUtensorMap* m) { asm volatile("prefetch.tensormap [%0];" :: "l"(m) : "memory"); }
__device__ __forceinline__ void fence_async() { asm volatile("fence.proxy.async.shared::cta;" ::: "memory"); }
__device__ __forceinline__ void wg_fence() { asm volatile("wgmma.fence.sync.aligned;" ::: "memory"); }
__device__ __forceinline__ void wg_commit() { asm volatile("wgmma.commit_group.sync.aligned;" ::: "memory"); }
template<int N> __device__ __forceinline__ void wg_wait() { asm volatile("wgmma.wait_group.sync.aligned %0;" :: "n"(N) : "memory"); }
__host__ __device__ constexpr uint64_t make_desc(uint32_t addr, uint32_t lbo, uint32_t sbo, uint64_t swz) {
  return (uint64_t)((addr & 0x3FFFF) >> 4) | ((uint64_t)(lbo >> 4) << 16) | ((uint64_t)(sbo >> 4) << 32) | (swz << 62);
}
template<int LO, int HI, int N> __device__ __forceinline__ void fence_regs(float (&a)[N]) {
  #pragma unroll
  for (int i = LO; i < HI; i++) asm volatile("" : "+f"(a[i]) :: "memory");
}
__device__ __forceinline__ uint32_t pack2(float lo, float hi) { uint32_t r; asm("cvt.rn.bf16x2.f32 %0, %1, %2;" : "=r"(r) : "f"(hi), "f"(lo)); return r; }
__device__ __forceinline__ void ldsm4(uint32_t& a, uint32_t& b, uint32_t& c, uint32_t& d, uint32_t addr) {
  asm volatile("ldmatrix.sync.aligned.m8n8.x4.shared.b16 {%0, %1, %2, %3}, [%4];" : "=r"(a), "=r"(b), "=r"(c), "=r"(d) : "r"(addr) : "memory");
}
__device__ __forceinline__ void stsm4(uint32_t addr, uint32_t a, uint32_t b, uint32_t c, uint32_t d) {
  asm volatile("stmatrix.sync.aligned.m8n8.x4.shared.b16 [%0], {%1, %2, %3, %4};" :: "r"(addr), "r"(a), "r"(b), "r"(c), "r"(d) : "memory");
}
__device__ __forceinline__ void mma_rowsum(float (&c)[4], uint32_t a0, uint32_t a1, uint32_t a2, uint32_t a3) {
  asm volatile("mma.sync.aligned.m16n8k16.row.col.f32.bf16.bf16.f32 {%0,%1,%2,%3}, {%4,%5,%6,%7}, {%8,%8}, {%0,%1,%2,%3};"
    : "+f"(c[0]), "+f"(c[1]), "+f"(c[2]), "+f"(c[3]) : "r"(a0), "r"(a1), "r"(a2), "r"(a3), "r"(0x3F803F80u));
}
__device__ __forceinline__ uint32_t hsub2(uint32_t a, uint32_t b) { uint32_t r; asm("sub.rn.bf16x2 %0, %1, %2;" : "=r"(r) : "r"(a), "r"(b)); return r; }
__device__ __forceinline__ uint32_t hadd2(uint32_t a, uint32_t b) { uint32_t r; asm("add.rn.bf16x2 %0, %1, %2;" : "=r"(r) : "r"(a), "r"(b)); return r; }
__device__ __forceinline__ uint32_t hfma2(uint32_t a, uint32_t b, uint32_t c) { uint32_t r; asm("fma.rn.bf16x2 %0, %1, %2, %3;" : "=r"(r) : "r"(a), "r"(b), "r"(c)); return r; }
__device__ __forceinline__ void warp_arrive(uint32_t bar) {
  __syncwarp();
  asm volatile("{\n.reg .pred p;\nelect.sync _|p, 0xffffffff;\n@p mbarrier.arrive.shared::cta.b64 _, [%0];\n}" :: "r"(bar) : "memory");
}
__device__ __forceinline__ void pin2(uint32_t& a, uint32_t& b) {
  asm volatile("{\n.reg .u32 c;\nmov.u32 c, %%clock;\nlop3.b32 %0, %0, c, %2, 0xF8;\nlop3.b32 %1, %1, c, %2, 0xF8;\n}" : "+r"(a), "+r"(b) : "r"(blockIdx.y) : "memory");
}
__device__ __forceinline__ float bf_lo(uint32_t u) { return __uint_as_float(u << 16); }
__device__ __forceinline__ float bf_hi(uint32_t u) { return __uint_as_float(u & 0xFFFF0000u); }
__device__ __forceinline__ float bf_round(float x) { return bf_lo(pack2(x, 0.f)); }
__device__ __forceinline__ float ex2(float x) { float r; asm("ex2.approx.ftz.f32 %0, %1;" : "=f"(r) : "f"(x)); return r; }
__device__ __forceinline__ float rcp(float x) { float r; asm("rcp.approx.ftz.f32 %0, %1;" : "=f"(r) : "f"(x)); return r; }
__device__ __forceinline__ float sqrt_approx(float x) { float r; asm("sqrt.approx.ftz.f32 %0, %1;" : "=f"(r) : "f"(x)); return r; }
__device__ __forceinline__ uint32_t phi2(float a0, float a1, float r, float rl) {
  const float e0 = __saturatef(ex2(a0 * rl) + 1e-6f), e1 = __saturatef(ex2(a1 * rl) + 1e-6f);
  return pack2(fmaxf(fmaf(a0, r, 1.000001f), e0), fmaxf(fmaf(a1, r, 1.000001f), e1));
}
__device__ __forceinline__ float geglu1(float g, float u, float c0, float c1, float c2) {
  float t = fmaf(g * g, c1, c0) * g, th;
  asm("tanh.approx.f32 %0, %1;" : "=f"(th) : "f"(t));
  float hh = g * u * c2;
  return fmaf(hh, th, hh);
}

template<int SD, uint64_t AD, uint64_t BD, int SZ> __device__ __forceinline__ void wg_ss128(float (&d)[SZ], uint32_t aoff) {
  if constexpr (SD == 0)
  asm volatile("{\n.reg .pred p;\n.reg .b64 ad, bd;\n.reg .b32 lo;\nsetp.ne.b32 p, 0, 0;\n"
    "add.u32 lo, %64, %65;\nmov.b64 ad, {lo, %66};\n"
    "mov.b64 bd, %67;\n"
    "wgmma.mma_async.sync.aligned.m64n128k16.f32.bf16.bf16 "
    "{%0, %1, %2, %3, %4, %5, %6, %7, %8, %9, %10, %11, %12, %13, %14, %15, %16, %17, %18, %19, %20, %21, %22, %23, %24, %25, %26, %27, %28, %29, %30, %31, %32, %33, %34, %35, %36, %37, %38, %39, %40, %41, %42, %43, %44, %45, %46, %47, %48, %49, %50, %51, %52, %53, %54, %55, %56, %57, %58, %59, %60, %61, %62, %63}, "
    "ad, bd, p, 1, 1, 0, 1;\n}\n"
    : "=f"(d[0]), "=f"(d[1]), "=f"(d[2]), "=f"(d[3]), "=f"(d[4]), "=f"(d[5]), "=f"(d[6]), "=f"(d[7]), "=f"(d[8]), "=f"(d[9]), "=f"(d[10]), "=f"(d[11]), "=f"(d[12]), "=f"(d[13]), "=f"(d[14]), "=f"(d[15]), "=f"(d[16]), "=f"(d[17]), "=f"(d[18]), "=f"(d[19]), "=f"(d[20]), "=f"(d[21]), "=f"(d[22]), "=f"(d[23]), "=f"(d[24]), "=f"(d[25]), "=f"(d[26]), "=f"(d[27]), "=f"(d[28]), "=f"(d[29]), "=f"(d[30]), "=f"(d[31]), "=f"(d[32]), "=f"(d[33]), "=f"(d[34]), "=f"(d[35]), "=f"(d[36]), "=f"(d[37]), "=f"(d[38]), "=f"(d[39]), "=f"(d[40]), "=f"(d[41]), "=f"(d[42]), "=f"(d[43]), "=f"(d[44]), "=f"(d[45]), "=f"(d[46]), "=f"(d[47]), "=f"(d[48]), "=f"(d[49]), "=f"(d[50]), "=f"(d[51]), "=f"(d[52]), "=f"(d[53]), "=f"(d[54]), "=f"(d[55]), "=f"(d[56]), "=f"(d[57]), "=f"(d[58]), "=f"(d[59]), "=f"(d[60]), "=f"(d[61]), "=f"(d[62]), "=f"(d[63])
    : "r"(aoff), "n"((uint32_t)AD), "n"((uint32_t)(AD >> 32)), "n"(BD));
  if constexpr (SD == 1)
  asm volatile("{\n.reg .pred p;\n.reg .b64 ad, bd;\n.reg .b32 lo;\nsetp.ne.b32 p, 1, 0;\n"
    "add.u32 lo, %64, %65;\nmov.b64 ad, {lo, %66};\n"
    "mov.b64 bd, %67;\n"
    "wgmma.mma_async.sync.aligned.m64n128k16.f32.bf16.bf16 "
    "{%0, %1, %2, %3, %4, %5, %6, %7, %8, %9, %10, %11, %12, %13, %14, %15, %16, %17, %18, %19, %20, %21, %22, %23, %24, %25, %26, %27, %28, %29, %30, %31, %32, %33, %34, %35, %36, %37, %38, %39, %40, %41, %42, %43, %44, %45, %46, %47, %48, %49, %50, %51, %52, %53, %54, %55, %56, %57, %58, %59, %60, %61, %62, %63}, "
    "ad, bd, p, 1, 1, 0, 1;\n}\n"
    : "+f"(d[0]), "+f"(d[1]), "+f"(d[2]), "+f"(d[3]), "+f"(d[4]), "+f"(d[5]), "+f"(d[6]), "+f"(d[7]), "+f"(d[8]), "+f"(d[9]), "+f"(d[10]), "+f"(d[11]), "+f"(d[12]), "+f"(d[13]), "+f"(d[14]), "+f"(d[15]), "+f"(d[16]), "+f"(d[17]), "+f"(d[18]), "+f"(d[19]), "+f"(d[20]), "+f"(d[21]), "+f"(d[22]), "+f"(d[23]), "+f"(d[24]), "+f"(d[25]), "+f"(d[26]), "+f"(d[27]), "+f"(d[28]), "+f"(d[29]), "+f"(d[30]), "+f"(d[31]), "+f"(d[32]), "+f"(d[33]), "+f"(d[34]), "+f"(d[35]), "+f"(d[36]), "+f"(d[37]), "+f"(d[38]), "+f"(d[39]), "+f"(d[40]), "+f"(d[41]), "+f"(d[42]), "+f"(d[43]), "+f"(d[44]), "+f"(d[45]), "+f"(d[46]), "+f"(d[47]), "+f"(d[48]), "+f"(d[49]), "+f"(d[50]), "+f"(d[51]), "+f"(d[52]), "+f"(d[53]), "+f"(d[54]), "+f"(d[55]), "+f"(d[56]), "+f"(d[57]), "+f"(d[58]), "+f"(d[59]), "+f"(d[60]), "+f"(d[61]), "+f"(d[62]), "+f"(d[63])
    : "r"(aoff), "n"((uint32_t)AD), "n"((uint32_t)(AD >> 32)), "n"(BD));
}
template<int SD, uint64_t AD, uint64_t BD, int SZ> __device__ __forceinline__ void wg_ss120(float (&d)[SZ], uint32_t aoff) {
  if constexpr (SD == 0)
  asm volatile("{\n.reg .pred p;\n.reg .b64 ad, bd;\n.reg .b32 lo;\nsetp.ne.b32 p, 0, 0;\n"
    "add.u32 lo, %60, %61;\nmov.b64 ad, {lo, %62};\n"
    "mov.b64 bd, %63;\n"
    "wgmma.mma_async.sync.aligned.m64n120k16.f32.bf16.bf16 "
    "{%0, %1, %2, %3, %4, %5, %6, %7, %8, %9, %10, %11, %12, %13, %14, %15, %16, %17, %18, %19, %20, %21, %22, %23, %24, %25, %26, %27, %28, %29, %30, %31, %32, %33, %34, %35, %36, %37, %38, %39, %40, %41, %42, %43, %44, %45, %46, %47, %48, %49, %50, %51, %52, %53, %54, %55, %56, %57, %58, %59}, "
    "ad, bd, p, 1, 1, 0, 1;\n}\n"
    : "=f"(d[0]), "=f"(d[1]), "=f"(d[2]), "=f"(d[3]), "=f"(d[4]), "=f"(d[5]), "=f"(d[6]), "=f"(d[7]), "=f"(d[8]), "=f"(d[9]), "=f"(d[10]), "=f"(d[11]), "=f"(d[12]), "=f"(d[13]), "=f"(d[14]), "=f"(d[15]), "=f"(d[16]), "=f"(d[17]), "=f"(d[18]), "=f"(d[19]), "=f"(d[20]), "=f"(d[21]), "=f"(d[22]), "=f"(d[23]), "=f"(d[24]), "=f"(d[25]), "=f"(d[26]), "=f"(d[27]), "=f"(d[28]), "=f"(d[29]), "=f"(d[30]), "=f"(d[31]), "=f"(d[32]), "=f"(d[33]), "=f"(d[34]), "=f"(d[35]), "=f"(d[36]), "=f"(d[37]), "=f"(d[38]), "=f"(d[39]), "=f"(d[40]), "=f"(d[41]), "=f"(d[42]), "=f"(d[43]), "=f"(d[44]), "=f"(d[45]), "=f"(d[46]), "=f"(d[47]), "=f"(d[48]), "=f"(d[49]), "=f"(d[50]), "=f"(d[51]), "=f"(d[52]), "=f"(d[53]), "=f"(d[54]), "=f"(d[55]), "=f"(d[56]), "=f"(d[57]), "=f"(d[58]), "=f"(d[59])
    : "r"(aoff), "n"((uint32_t)AD), "n"((uint32_t)(AD >> 32)), "n"(BD));
  if constexpr (SD == 1)
  asm volatile("{\n.reg .pred p;\n.reg .b64 ad, bd;\n.reg .b32 lo;\nsetp.ne.b32 p, 1, 0;\n"
    "add.u32 lo, %60, %61;\nmov.b64 ad, {lo, %62};\n"
    "mov.b64 bd, %63;\n"
    "wgmma.mma_async.sync.aligned.m64n120k16.f32.bf16.bf16 "
    "{%0, %1, %2, %3, %4, %5, %6, %7, %8, %9, %10, %11, %12, %13, %14, %15, %16, %17, %18, %19, %20, %21, %22, %23, %24, %25, %26, %27, %28, %29, %30, %31, %32, %33, %34, %35, %36, %37, %38, %39, %40, %41, %42, %43, %44, %45, %46, %47, %48, %49, %50, %51, %52, %53, %54, %55, %56, %57, %58, %59}, "
    "ad, bd, p, 1, 1, 0, 1;\n}\n"
    : "+f"(d[0]), "+f"(d[1]), "+f"(d[2]), "+f"(d[3]), "+f"(d[4]), "+f"(d[5]), "+f"(d[6]), "+f"(d[7]), "+f"(d[8]), "+f"(d[9]), "+f"(d[10]), "+f"(d[11]), "+f"(d[12]), "+f"(d[13]), "+f"(d[14]), "+f"(d[15]), "+f"(d[16]), "+f"(d[17]), "+f"(d[18]), "+f"(d[19]), "+f"(d[20]), "+f"(d[21]), "+f"(d[22]), "+f"(d[23]), "+f"(d[24]), "+f"(d[25]), "+f"(d[26]), "+f"(d[27]), "+f"(d[28]), "+f"(d[29]), "+f"(d[30]), "+f"(d[31]), "+f"(d[32]), "+f"(d[33]), "+f"(d[34]), "+f"(d[35]), "+f"(d[36]), "+f"(d[37]), "+f"(d[38]), "+f"(d[39]), "+f"(d[40]), "+f"(d[41]), "+f"(d[42]), "+f"(d[43]), "+f"(d[44]), "+f"(d[45]), "+f"(d[46]), "+f"(d[47]), "+f"(d[48]), "+f"(d[49]), "+f"(d[50]), "+f"(d[51]), "+f"(d[52]), "+f"(d[53]), "+f"(d[54]), "+f"(d[55]), "+f"(d[56]), "+f"(d[57]), "+f"(d[58]), "+f"(d[59])
    : "r"(aoff), "n"((uint32_t)AD), "n"((uint32_t)(AD >> 32)), "n"(BD));
}
template<int SD, uint64_t AD, uint64_t BD, int SZ> __device__ __forceinline__ void wg_ss40t(float (&d)[SZ], uint32_t aoff) {
  if constexpr (SD == 0)
  asm volatile("{\n.reg .pred p;\n.reg .b64 ad, bd;\n.reg .b32 lo;\nsetp.ne.b32 p, 0, 0;\n"
    "mov.u32 lo, %21;\nmov.b64 ad, {lo, %22};\n"
    "add.u32 lo, %20, %23;\nmov.b64 bd, {lo, %24};\n"
    "wgmma.mma_async.sync.aligned.m64n40k16.f32.bf16.bf16 "
    "{%0, %1, %2, %3, %4, %5, %6, %7, %8, %9, %10, %11, %12, %13, %14, %15, %16, %17, %18, %19}, "
    "ad, bd, p, 1, 1, 1, 1;\n}\n"
    : "=f"(d[0]), "=f"(d[1]), "=f"(d[2]), "=f"(d[3]), "=f"(d[4]), "=f"(d[5]), "=f"(d[6]), "=f"(d[7]), "=f"(d[8]), "=f"(d[9]), "=f"(d[10]), "=f"(d[11]), "=f"(d[12]), "=f"(d[13]), "=f"(d[14]), "=f"(d[15]), "=f"(d[16]), "=f"(d[17]), "=f"(d[18]), "=f"(d[19])
    : "r"(aoff), "n"((uint32_t)AD), "n"((uint32_t)(AD >> 32)), "n"((uint32_t)BD), "n"((uint32_t)(BD >> 32)));
  if constexpr (SD == 1)
  asm volatile("{\n.reg .pred p;\n.reg .b64 ad, bd;\n.reg .b32 lo;\nsetp.ne.b32 p, 1, 0;\n"
    "mov.u32 lo, %21;\nmov.b64 ad, {lo, %22};\n"
    "add.u32 lo, %20, %23;\nmov.b64 bd, {lo, %24};\n"
    "wgmma.mma_async.sync.aligned.m64n40k16.f32.bf16.bf16 "
    "{%0, %1, %2, %3, %4, %5, %6, %7, %8, %9, %10, %11, %12, %13, %14, %15, %16, %17, %18, %19}, "
    "ad, bd, p, 1, 1, 1, 1;\n}\n"
    : "+f"(d[0]), "+f"(d[1]), "+f"(d[2]), "+f"(d[3]), "+f"(d[4]), "+f"(d[5]), "+f"(d[6]), "+f"(d[7]), "+f"(d[8]), "+f"(d[9]), "+f"(d[10]), "+f"(d[11]), "+f"(d[12]), "+f"(d[13]), "+f"(d[14]), "+f"(d[15]), "+f"(d[16]), "+f"(d[17]), "+f"(d[18]), "+f"(d[19])
    : "r"(aoff), "n"((uint32_t)AD), "n"((uint32_t)(AD >> 32)), "n"((uint32_t)BD), "n"((uint32_t)(BD >> 32)));
}
template<int SD, uint64_t BD, int SZ> __device__ __forceinline__ void wg_rs128(float (&d)[SZ], uint32_t a0, uint32_t a1, uint32_t a2, uint32_t a3) {
  if constexpr (SD == 0)
  asm volatile("{\n.reg .pred p;\n.reg .b64 ad, bd;\n.reg .b32 lo;\nsetp.ne.b32 p, 0, 0;\n"
    "mov.b64 bd, %68;\n"
    "wgmma.mma_async.sync.aligned.m64n128k16.f32.bf16.bf16 "
    "{%0, %1, %2, %3, %4, %5, %6, %7, %8, %9, %10, %11, %12, %13, %14, %15, %16, %17, %18, %19, %20, %21, %22, %23, %24, %25, %26, %27, %28, %29, %30, %31, %32, %33, %34, %35, %36, %37, %38, %39, %40, %41, %42, %43, %44, %45, %46, %47, %48, %49, %50, %51, %52, %53, %54, %55, %56, %57, %58, %59, %60, %61, %62, %63}, "
    "{%64, %65, %66, %67}, bd, p, 1, 1, 1;\n}\n"
    : "=f"(d[0]), "=f"(d[1]), "=f"(d[2]), "=f"(d[3]), "=f"(d[4]), "=f"(d[5]), "=f"(d[6]), "=f"(d[7]), "=f"(d[8]), "=f"(d[9]), "=f"(d[10]), "=f"(d[11]), "=f"(d[12]), "=f"(d[13]), "=f"(d[14]), "=f"(d[15]), "=f"(d[16]), "=f"(d[17]), "=f"(d[18]), "=f"(d[19]), "=f"(d[20]), "=f"(d[21]), "=f"(d[22]), "=f"(d[23]), "=f"(d[24]), "=f"(d[25]), "=f"(d[26]), "=f"(d[27]), "=f"(d[28]), "=f"(d[29]), "=f"(d[30]), "=f"(d[31]), "=f"(d[32]), "=f"(d[33]), "=f"(d[34]), "=f"(d[35]), "=f"(d[36]), "=f"(d[37]), "=f"(d[38]), "=f"(d[39]), "=f"(d[40]), "=f"(d[41]), "=f"(d[42]), "=f"(d[43]), "=f"(d[44]), "=f"(d[45]), "=f"(d[46]), "=f"(d[47]), "=f"(d[48]), "=f"(d[49]), "=f"(d[50]), "=f"(d[51]), "=f"(d[52]), "=f"(d[53]), "=f"(d[54]), "=f"(d[55]), "=f"(d[56]), "=f"(d[57]), "=f"(d[58]), "=f"(d[59]), "=f"(d[60]), "=f"(d[61]), "=f"(d[62]), "=f"(d[63])
    : "r"(a0), "r"(a1), "r"(a2), "r"(a3), "n"(BD));
  if constexpr (SD == 1)
  asm volatile("{\n.reg .pred p;\n.reg .b64 ad, bd;\n.reg .b32 lo;\nsetp.ne.b32 p, 1, 0;\n"
    "mov.b64 bd, %68;\n"
    "wgmma.mma_async.sync.aligned.m64n128k16.f32.bf16.bf16 "
    "{%0, %1, %2, %3, %4, %5, %6, %7, %8, %9, %10, %11, %12, %13, %14, %15, %16, %17, %18, %19, %20, %21, %22, %23, %24, %25, %26, %27, %28, %29, %30, %31, %32, %33, %34, %35, %36, %37, %38, %39, %40, %41, %42, %43, %44, %45, %46, %47, %48, %49, %50, %51, %52, %53, %54, %55, %56, %57, %58, %59, %60, %61, %62, %63}, "
    "{%64, %65, %66, %67}, bd, p, 1, 1, 1;\n}\n"
    : "+f"(d[0]), "+f"(d[1]), "+f"(d[2]), "+f"(d[3]), "+f"(d[4]), "+f"(d[5]), "+f"(d[6]), "+f"(d[7]), "+f"(d[8]), "+f"(d[9]), "+f"(d[10]), "+f"(d[11]), "+f"(d[12]), "+f"(d[13]), "+f"(d[14]), "+f"(d[15]), "+f"(d[16]), "+f"(d[17]), "+f"(d[18]), "+f"(d[19]), "+f"(d[20]), "+f"(d[21]), "+f"(d[22]), "+f"(d[23]), "+f"(d[24]), "+f"(d[25]), "+f"(d[26]), "+f"(d[27]), "+f"(d[28]), "+f"(d[29]), "+f"(d[30]), "+f"(d[31]), "+f"(d[32]), "+f"(d[33]), "+f"(d[34]), "+f"(d[35]), "+f"(d[36]), "+f"(d[37]), "+f"(d[38]), "+f"(d[39]), "+f"(d[40]), "+f"(d[41]), "+f"(d[42]), "+f"(d[43]), "+f"(d[44]), "+f"(d[45]), "+f"(d[46]), "+f"(d[47]), "+f"(d[48]), "+f"(d[49]), "+f"(d[50]), "+f"(d[51]), "+f"(d[52]), "+f"(d[53]), "+f"(d[54]), "+f"(d[55]), "+f"(d[56]), "+f"(d[57]), "+f"(d[58]), "+f"(d[59]), "+f"(d[60]), "+f"(d[61]), "+f"(d[62]), "+f"(d[63])
    : "r"(a0), "r"(a1), "r"(a2), "r"(a3), "n"(BD));
}
template<int SD, uint64_t BD, int SZ> __device__ __forceinline__ void wg_rs120(float (&d)[SZ], uint32_t a0, uint32_t a1, uint32_t a2, uint32_t a3, uint32_t boff) {
  if constexpr (SD == 0)
  asm volatile("{\n.reg .pred p;\n.reg .b64 ad, bd;\n.reg .b32 lo;\nsetp.ne.b32 p, 0, 0;\n"
    "add.u32 lo, %64, %65;\nmov.b64 bd, {lo, %66};\n"
    "wgmma.mma_async.sync.aligned.m64n120k16.f32.bf16.bf16 "
    "{%0, %1, %2, %3, %4, %5, %6, %7, %8, %9, %10, %11, %12, %13, %14, %15, %16, %17, %18, %19, %20, %21, %22, %23, %24, %25, %26, %27, %28, %29, %30, %31, %32, %33, %34, %35, %36, %37, %38, %39, %40, %41, %42, %43, %44, %45, %46, %47, %48, %49, %50, %51, %52, %53, %54, %55, %56, %57, %58, %59}, "
    "{%60, %61, %62, %63}, bd, p, 1, 1, 1;\n}\n"
    : "=f"(d[0]), "=f"(d[1]), "=f"(d[2]), "=f"(d[3]), "=f"(d[4]), "=f"(d[5]), "=f"(d[6]), "=f"(d[7]), "=f"(d[8]), "=f"(d[9]), "=f"(d[10]), "=f"(d[11]), "=f"(d[12]), "=f"(d[13]), "=f"(d[14]), "=f"(d[15]), "=f"(d[16]), "=f"(d[17]), "=f"(d[18]), "=f"(d[19]), "=f"(d[20]), "=f"(d[21]), "=f"(d[22]), "=f"(d[23]), "=f"(d[24]), "=f"(d[25]), "=f"(d[26]), "=f"(d[27]), "=f"(d[28]), "=f"(d[29]), "=f"(d[30]), "=f"(d[31]), "=f"(d[32]), "=f"(d[33]), "=f"(d[34]), "=f"(d[35]), "=f"(d[36]), "=f"(d[37]), "=f"(d[38]), "=f"(d[39]), "=f"(d[40]), "=f"(d[41]), "=f"(d[42]), "=f"(d[43]), "=f"(d[44]), "=f"(d[45]), "=f"(d[46]), "=f"(d[47]), "=f"(d[48]), "=f"(d[49]), "=f"(d[50]), "=f"(d[51]), "=f"(d[52]), "=f"(d[53]), "=f"(d[54]), "=f"(d[55]), "=f"(d[56]), "=f"(d[57]), "=f"(d[58]), "=f"(d[59])
    : "r"(a0), "r"(a1), "r"(a2), "r"(a3), "r"(boff), "n"((uint32_t)BD), "n"((uint32_t)(BD >> 32)));
  if constexpr (SD == 1)
  asm volatile("{\n.reg .pred p;\n.reg .b64 ad, bd;\n.reg .b32 lo;\nsetp.ne.b32 p, 1, 0;\n"
    "add.u32 lo, %64, %65;\nmov.b64 bd, {lo, %66};\n"
    "wgmma.mma_async.sync.aligned.m64n120k16.f32.bf16.bf16 "
    "{%0, %1, %2, %3, %4, %5, %6, %7, %8, %9, %10, %11, %12, %13, %14, %15, %16, %17, %18, %19, %20, %21, %22, %23, %24, %25, %26, %27, %28, %29, %30, %31, %32, %33, %34, %35, %36, %37, %38, %39, %40, %41, %42, %43, %44, %45, %46, %47, %48, %49, %50, %51, %52, %53, %54, %55, %56, %57, %58, %59}, "
    "{%60, %61, %62, %63}, bd, p, 1, 1, 1;\n}\n"
    : "+f"(d[0]), "+f"(d[1]), "+f"(d[2]), "+f"(d[3]), "+f"(d[4]), "+f"(d[5]), "+f"(d[6]), "+f"(d[7]), "+f"(d[8]), "+f"(d[9]), "+f"(d[10]), "+f"(d[11]), "+f"(d[12]), "+f"(d[13]), "+f"(d[14]), "+f"(d[15]), "+f"(d[16]), "+f"(d[17]), "+f"(d[18]), "+f"(d[19]), "+f"(d[20]), "+f"(d[21]), "+f"(d[22]), "+f"(d[23]), "+f"(d[24]), "+f"(d[25]), "+f"(d[26]), "+f"(d[27]), "+f"(d[28]), "+f"(d[29]), "+f"(d[30]), "+f"(d[31]), "+f"(d[32]), "+f"(d[33]), "+f"(d[34]), "+f"(d[35]), "+f"(d[36]), "+f"(d[37]), "+f"(d[38]), "+f"(d[39]), "+f"(d[40]), "+f"(d[41]), "+f"(d[42]), "+f"(d[43]), "+f"(d[44]), "+f"(d[45]), "+f"(d[46]), "+f"(d[47]), "+f"(d[48]), "+f"(d[49]), "+f"(d[50]), "+f"(d[51]), "+f"(d[52]), "+f"(d[53]), "+f"(d[54]), "+f"(d[55]), "+f"(d[56]), "+f"(d[57]), "+f"(d[58]), "+f"(d[59])
    : "r"(a0), "r"(a1), "r"(a2), "r"(a3), "r"(boff), "n"((uint32_t)BD), "n"((uint32_t)(BD >> 32)));
}
template<int SD, uint64_t AD, uint64_t BD, int SZ> __device__ __forceinline__ void wg_ss120b(float (&d)[SZ], uint32_t aoff, uint32_t boff) {
  if constexpr (SD == 0)
  asm volatile("{\n.reg .pred p;\n.reg .b64 ad, bd;\n.reg .b32 lo;\nsetp.ne.b32 p, 0, 0;\n"
    "add.u32 lo, %60, %61;\nmov.b64 ad, {lo, %62};\n"
    "add.u32 lo, %63, %64;\nmov.b64 bd, {lo, %65};\n"
    "wgmma.mma_async.sync.aligned.m64n120k16.f32.bf16.bf16 "
    "{%0, %1, %2, %3, %4, %5, %6, %7, %8, %9, %10, %11, %12, %13, %14, %15, %16, %17, %18, %19, %20, %21, %22, %23, %24, %25, %26, %27, %28, %29, %30, %31, %32, %33, %34, %35, %36, %37, %38, %39, %40, %41, %42, %43, %44, %45, %46, %47, %48, %49, %50, %51, %52, %53, %54, %55, %56, %57, %58, %59}, "
    "ad, bd, p, 1, 1, 0, 1;\n}\n"
    : "=f"(d[0]), "=f"(d[1]), "=f"(d[2]), "=f"(d[3]), "=f"(d[4]), "=f"(d[5]), "=f"(d[6]), "=f"(d[7]), "=f"(d[8]), "=f"(d[9]), "=f"(d[10]), "=f"(d[11]), "=f"(d[12]), "=f"(d[13]), "=f"(d[14]), "=f"(d[15]), "=f"(d[16]), "=f"(d[17]), "=f"(d[18]), "=f"(d[19]), "=f"(d[20]), "=f"(d[21]), "=f"(d[22]), "=f"(d[23]), "=f"(d[24]), "=f"(d[25]), "=f"(d[26]), "=f"(d[27]), "=f"(d[28]), "=f"(d[29]), "=f"(d[30]), "=f"(d[31]), "=f"(d[32]), "=f"(d[33]), "=f"(d[34]), "=f"(d[35]), "=f"(d[36]), "=f"(d[37]), "=f"(d[38]), "=f"(d[39]), "=f"(d[40]), "=f"(d[41]), "=f"(d[42]), "=f"(d[43]), "=f"(d[44]), "=f"(d[45]), "=f"(d[46]), "=f"(d[47]), "=f"(d[48]), "=f"(d[49]), "=f"(d[50]), "=f"(d[51]), "=f"(d[52]), "=f"(d[53]), "=f"(d[54]), "=f"(d[55]), "=f"(d[56]), "=f"(d[57]), "=f"(d[58]), "=f"(d[59])
    : "r"(aoff), "n"((uint32_t)AD), "n"((uint32_t)(AD >> 32)), "r"(boff), "n"((uint32_t)BD), "n"((uint32_t)(BD >> 32)));
  if constexpr (SD == 1)
  asm volatile("{\n.reg .pred p;\n.reg .b64 ad, bd;\n.reg .b32 lo;\nsetp.ne.b32 p, 1, 0;\n"
    "add.u32 lo, %60, %61;\nmov.b64 ad, {lo, %62};\n"
    "add.u32 lo, %63, %64;\nmov.b64 bd, {lo, %65};\n"
    "wgmma.mma_async.sync.aligned.m64n120k16.f32.bf16.bf16 "
    "{%0, %1, %2, %3, %4, %5, %6, %7, %8, %9, %10, %11, %12, %13, %14, %15, %16, %17, %18, %19, %20, %21, %22, %23, %24, %25, %26, %27, %28, %29, %30, %31, %32, %33, %34, %35, %36, %37, %38, %39, %40, %41, %42, %43, %44, %45, %46, %47, %48, %49, %50, %51, %52, %53, %54, %55, %56, %57, %58, %59}, "
    "ad, bd, p, 1, 1, 0, 1;\n}\n"
    : "+f"(d[0]), "+f"(d[1]), "+f"(d[2]), "+f"(d[3]), "+f"(d[4]), "+f"(d[5]), "+f"(d[6]), "+f"(d[7]), "+f"(d[8]), "+f"(d[9]), "+f"(d[10]), "+f"(d[11]), "+f"(d[12]), "+f"(d[13]), "+f"(d[14]), "+f"(d[15]), "+f"(d[16]), "+f"(d[17]), "+f"(d[18]), "+f"(d[19]), "+f"(d[20]), "+f"(d[21]), "+f"(d[22]), "+f"(d[23]), "+f"(d[24]), "+f"(d[25]), "+f"(d[26]), "+f"(d[27]), "+f"(d[28]), "+f"(d[29]), "+f"(d[30]), "+f"(d[31]), "+f"(d[32]), "+f"(d[33]), "+f"(d[34]), "+f"(d[35]), "+f"(d[36]), "+f"(d[37]), "+f"(d[38]), "+f"(d[39]), "+f"(d[40]), "+f"(d[41]), "+f"(d[42]), "+f"(d[43]), "+f"(d[44]), "+f"(d[45]), "+f"(d[46]), "+f"(d[47]), "+f"(d[48]), "+f"(d[49]), "+f"(d[50]), "+f"(d[51]), "+f"(d[52]), "+f"(d[53]), "+f"(d[54]), "+f"(d[55]), "+f"(d[56]), "+f"(d[57]), "+f"(d[58]), "+f"(d[59])
    : "r"(aoff), "n"((uint32_t)AD), "n"((uint32_t)(AD >> 32)), "r"(boff), "n"((uint32_t)BD), "n"((uint32_t)(BD >> 32)));
}
template<int SD, uint64_t BD, int SZ> __device__ __forceinline__ void wg_rs64(float (&d)[SZ], uint32_t a0, uint32_t a1, uint32_t a2, uint32_t a3) {
  if constexpr (SD == 0)
  asm volatile("{\n.reg .pred p;\n.reg .b64 ad, bd;\n.reg .b32 lo;\nsetp.ne.b32 p, 0, 0;\n"
    "mov.b64 bd, %36;\n"
    "wgmma.mma_async.sync.aligned.m64n64k16.f32.bf16.bf16 "
    "{%0, %1, %2, %3, %4, %5, %6, %7, %8, %9, %10, %11, %12, %13, %14, %15, %16, %17, %18, %19, %20, %21, %22, %23, %24, %25, %26, %27, %28, %29, %30, %31}, "
    "{%32, %33, %34, %35}, bd, p, 1, 1, 1;\n}\n"
    : "=f"(d[0]), "=f"(d[1]), "=f"(d[2]), "=f"(d[3]), "=f"(d[4]), "=f"(d[5]), "=f"(d[6]), "=f"(d[7]), "=f"(d[8]), "=f"(d[9]), "=f"(d[10]), "=f"(d[11]), "=f"(d[12]), "=f"(d[13]), "=f"(d[14]), "=f"(d[15]), "=f"(d[16]), "=f"(d[17]), "=f"(d[18]), "=f"(d[19]), "=f"(d[20]), "=f"(d[21]), "=f"(d[22]), "=f"(d[23]), "=f"(d[24]), "=f"(d[25]), "=f"(d[26]), "=f"(d[27]), "=f"(d[28]), "=f"(d[29]), "=f"(d[30]), "=f"(d[31])
    : "r"(a0), "r"(a1), "r"(a2), "r"(a3), "n"(BD));
  if constexpr (SD == 1)
  asm volatile("{\n.reg .pred p;\n.reg .b64 ad, bd;\n.reg .b32 lo;\nsetp.ne.b32 p, 1, 0;\n"
    "mov.b64 bd, %36;\n"
    "wgmma.mma_async.sync.aligned.m64n64k16.f32.bf16.bf16 "
    "{%0, %1, %2, %3, %4, %5, %6, %7, %8, %9, %10, %11, %12, %13, %14, %15, %16, %17, %18, %19, %20, %21, %22, %23, %24, %25, %26, %27, %28, %29, %30, %31}, "
    "{%32, %33, %34, %35}, bd, p, 1, 1, 1;\n}\n"
    : "+f"(d[0]), "+f"(d[1]), "+f"(d[2]), "+f"(d[3]), "+f"(d[4]), "+f"(d[5]), "+f"(d[6]), "+f"(d[7]), "+f"(d[8]), "+f"(d[9]), "+f"(d[10]), "+f"(d[11]), "+f"(d[12]), "+f"(d[13]), "+f"(d[14]), "+f"(d[15]), "+f"(d[16]), "+f"(d[17]), "+f"(d[18]), "+f"(d[19]), "+f"(d[20]), "+f"(d[21]), "+f"(d[22]), "+f"(d[23]), "+f"(d[24]), "+f"(d[25]), "+f"(d[26]), "+f"(d[27]), "+f"(d[28]), "+f"(d[29]), "+f"(d[30]), "+f"(d[31])
    : "r"(a0), "r"(a1), "r"(a2), "r"(a3), "n"(BD));
}
template<int SD, uint64_t BD, int SZ> __device__ __forceinline__ void wg_rs64h(float (&d)[SZ], uint32_t a0, uint32_t a1, uint32_t a2, uint32_t a3) {
  if constexpr (SD == 0)
  asm volatile("{\n.reg .pred p;\n.reg .b64 ad, bd;\n.reg .b32 lo;\nsetp.ne.b32 p, 0, 0;\n"
    "mov.b64 bd, %36;\n"
    "wgmma.mma_async.sync.aligned.m64n64k16.f32.bf16.bf16 "
    "{%0, %1, %2, %3, %4, %5, %6, %7, %8, %9, %10, %11, %12, %13, %14, %15, %16, %17, %18, %19, %20, %21, %22, %23, %24, %25, %26, %27, %28, %29, %30, %31}, "
    "{%32, %33, %34, %35}, bd, p, 1, 1, 1;\n}\n"
    : "=f"(d[32]), "=f"(d[33]), "=f"(d[34]), "=f"(d[35]), "=f"(d[36]), "=f"(d[37]), "=f"(d[38]), "=f"(d[39]), "=f"(d[40]), "=f"(d[41]), "=f"(d[42]), "=f"(d[43]), "=f"(d[44]), "=f"(d[45]), "=f"(d[46]), "=f"(d[47]), "=f"(d[48]), "=f"(d[49]), "=f"(d[50]), "=f"(d[51]), "=f"(d[52]), "=f"(d[53]), "=f"(d[54]), "=f"(d[55]), "=f"(d[56]), "=f"(d[57]), "=f"(d[58]), "=f"(d[59]), "=f"(d[60]), "=f"(d[61]), "=f"(d[62]), "=f"(d[63])
    : "r"(a0), "r"(a1), "r"(a2), "r"(a3), "n"(BD));
  if constexpr (SD == 1)
  asm volatile("{\n.reg .pred p;\n.reg .b64 ad, bd;\n.reg .b32 lo;\nsetp.ne.b32 p, 1, 0;\n"
    "mov.b64 bd, %36;\n"
    "wgmma.mma_async.sync.aligned.m64n64k16.f32.bf16.bf16 "
    "{%0, %1, %2, %3, %4, %5, %6, %7, %8, %9, %10, %11, %12, %13, %14, %15, %16, %17, %18, %19, %20, %21, %22, %23, %24, %25, %26, %27, %28, %29, %30, %31}, "
    "{%32, %33, %34, %35}, bd, p, 1, 1, 1;\n}\n"
    : "+f"(d[32]), "+f"(d[33]), "+f"(d[34]), "+f"(d[35]), "+f"(d[36]), "+f"(d[37]), "+f"(d[38]), "+f"(d[39]), "+f"(d[40]), "+f"(d[41]), "+f"(d[42]), "+f"(d[43]), "+f"(d[44]), "+f"(d[45]), "+f"(d[46]), "+f"(d[47]), "+f"(d[48]), "+f"(d[49]), "+f"(d[50]), "+f"(d[51]), "+f"(d[52]), "+f"(d[53]), "+f"(d[54]), "+f"(d[55]), "+f"(d[56]), "+f"(d[57]), "+f"(d[58]), "+f"(d[59]), "+f"(d[60]), "+f"(d[61]), "+f"(d[62]), "+f"(d[63])
    : "r"(a0), "r"(a1), "r"(a2), "r"(a3), "n"(BD));
}
template<int SD, uint64_t AD, uint64_t BD, int SZ> __device__ __forceinline__ void wg_ss64(float (&d)[SZ], uint32_t aoff) {
  if constexpr (SD == 0)
  asm volatile("{\n.reg .pred p;\n.reg .b64 ad, bd;\n.reg .b32 lo;\nsetp.ne.b32 p, 0, 0;\n"
    "add.u32 lo, %32, %33;\nmov.b64 ad, {lo, %34};\n"
    "mov.b64 bd, %35;\n"
    "wgmma.mma_async.sync.aligned.m64n64k16.f32.bf16.bf16 "
    "{%0, %1, %2, %3, %4, %5, %6, %7, %8, %9, %10, %11, %12, %13, %14, %15, %16, %17, %18, %19, %20, %21, %22, %23, %24, %25, %26, %27, %28, %29, %30, %31}, "
    "ad, bd, p, 1, 1, 0, 1;\n}\n"
    : "=f"(d[0]), "=f"(d[1]), "=f"(d[2]), "=f"(d[3]), "=f"(d[4]), "=f"(d[5]), "=f"(d[6]), "=f"(d[7]), "=f"(d[8]), "=f"(d[9]), "=f"(d[10]), "=f"(d[11]), "=f"(d[12]), "=f"(d[13]), "=f"(d[14]), "=f"(d[15]), "=f"(d[16]), "=f"(d[17]), "=f"(d[18]), "=f"(d[19]), "=f"(d[20]), "=f"(d[21]), "=f"(d[22]), "=f"(d[23]), "=f"(d[24]), "=f"(d[25]), "=f"(d[26]), "=f"(d[27]), "=f"(d[28]), "=f"(d[29]), "=f"(d[30]), "=f"(d[31])
    : "r"(aoff), "n"((uint32_t)AD), "n"((uint32_t)(AD >> 32)), "n"(BD));
  if constexpr (SD == 1)
  asm volatile("{\n.reg .pred p;\n.reg .b64 ad, bd;\n.reg .b32 lo;\nsetp.ne.b32 p, 1, 0;\n"
    "add.u32 lo, %32, %33;\nmov.b64 ad, {lo, %34};\n"
    "mov.b64 bd, %35;\n"
    "wgmma.mma_async.sync.aligned.m64n64k16.f32.bf16.bf16 "
    "{%0, %1, %2, %3, %4, %5, %6, %7, %8, %9, %10, %11, %12, %13, %14, %15, %16, %17, %18, %19, %20, %21, %22, %23, %24, %25, %26, %27, %28, %29, %30, %31}, "
    "ad, bd, p, 1, 1, 0, 1;\n}\n"
    : "+f"(d[0]), "+f"(d[1]), "+f"(d[2]), "+f"(d[3]), "+f"(d[4]), "+f"(d[5]), "+f"(d[6]), "+f"(d[7]), "+f"(d[8]), "+f"(d[9]), "+f"(d[10]), "+f"(d[11]), "+f"(d[12]), "+f"(d[13]), "+f"(d[14]), "+f"(d[15]), "+f"(d[16]), "+f"(d[17]), "+f"(d[18]), "+f"(d[19]), "+f"(d[20]), "+f"(d[21]), "+f"(d[22]), "+f"(d[23]), "+f"(d[24]), "+f"(d[25]), "+f"(d[26]), "+f"(d[27]), "+f"(d[28]), "+f"(d[29]), "+f"(d[30]), "+f"(d[31])
    : "r"(aoff), "n"((uint32_t)AD), "n"((uint32_t)(AD >> 32)), "n"(BD));
}
template<int SD, uint64_t AD, uint64_t BD, int SZ> __device__ __forceinline__ void wg_ss64h(float (&d)[SZ], uint32_t aoff) {
  if constexpr (SD == 0)
  asm volatile("{\n.reg .pred p;\n.reg .b64 ad, bd;\n.reg .b32 lo;\nsetp.ne.b32 p, 0, 0;\n"
    "add.u32 lo, %32, %33;\nmov.b64 ad, {lo, %34};\n"
    "mov.b64 bd, %35;\n"
    "wgmma.mma_async.sync.aligned.m64n64k16.f32.bf16.bf16 "
    "{%0, %1, %2, %3, %4, %5, %6, %7, %8, %9, %10, %11, %12, %13, %14, %15, %16, %17, %18, %19, %20, %21, %22, %23, %24, %25, %26, %27, %28, %29, %30, %31}, "
    "ad, bd, p, 1, 1, 0, 1;\n}\n"
    : "=f"(d[32]), "=f"(d[33]), "=f"(d[34]), "=f"(d[35]), "=f"(d[36]), "=f"(d[37]), "=f"(d[38]), "=f"(d[39]), "=f"(d[40]), "=f"(d[41]), "=f"(d[42]), "=f"(d[43]), "=f"(d[44]), "=f"(d[45]), "=f"(d[46]), "=f"(d[47]), "=f"(d[48]), "=f"(d[49]), "=f"(d[50]), "=f"(d[51]), "=f"(d[52]), "=f"(d[53]), "=f"(d[54]), "=f"(d[55]), "=f"(d[56]), "=f"(d[57]), "=f"(d[58]), "=f"(d[59]), "=f"(d[60]), "=f"(d[61]), "=f"(d[62]), "=f"(d[63])
    : "r"(aoff), "n"((uint32_t)AD), "n"((uint32_t)(AD >> 32)), "n"(BD));
  if constexpr (SD == 1)
  asm volatile("{\n.reg .pred p;\n.reg .b64 ad, bd;\n.reg .b32 lo;\nsetp.ne.b32 p, 1, 0;\n"
    "add.u32 lo, %32, %33;\nmov.b64 ad, {lo, %34};\n"
    "mov.b64 bd, %35;\n"
    "wgmma.mma_async.sync.aligned.m64n64k16.f32.bf16.bf16 "
    "{%0, %1, %2, %3, %4, %5, %6, %7, %8, %9, %10, %11, %12, %13, %14, %15, %16, %17, %18, %19, %20, %21, %22, %23, %24, %25, %26, %27, %28, %29, %30, %31}, "
    "ad, bd, p, 1, 1, 0, 1;\n}\n"
    : "+f"(d[32]), "+f"(d[33]), "+f"(d[34]), "+f"(d[35]), "+f"(d[36]), "+f"(d[37]), "+f"(d[38]), "+f"(d[39]), "+f"(d[40]), "+f"(d[41]), "+f"(d[42]), "+f"(d[43]), "+f"(d[44]), "+f"(d[45]), "+f"(d[46]), "+f"(d[47]), "+f"(d[48]), "+f"(d[49]), "+f"(d[50]), "+f"(d[51]), "+f"(d[52]), "+f"(d[53]), "+f"(d[54]), "+f"(d[55]), "+f"(d[56]), "+f"(d[57]), "+f"(d[58]), "+f"(d[59]), "+f"(d[60]), "+f"(d[61]), "+f"(d[62]), "+f"(d[63])
    : "r"(aoff), "n"((uint32_t)AD), "n"((uint32_t)(AD >> 32)), "n"(BD));
}

constexpr uint64_t dB128 = make_desc(SB, 8192, 1024, 1);
constexpr uint64_t dB128h = make_desc(SB, 4096, 1024, 1);
constexpr uint64_t dB64 = make_desc(SB, 4096, 512, 2);
constexpr uint64_t dA = make_desc(SB + OFF_X, 16, 1024, 1);
template<int I> struct IC { static constexpr int value = I; };
template<int B, int E, class F> __device__ __forceinline__ void sfor(F&& f) { if constexpr (B < E) { f(IC<B>{}); sfor<B + 1, E>(f); } }
#define SFOR(VAR, B, E) sfor<B, E>([&](auto VAR##_) __attribute__((always_inline)) { constexpr int VAR = decltype(VAR##_)::value;
#define SEND });

struct RowC { float c0, c1, c2; };

template<int LO, int HI, int NPR, int HOFF>
__device__ __forceinline__ void geglu_slice(uint32_t (&hp)[56], float (&acc)[64], const RowC& a, const RowC& b) {
  #pragma unroll
  for (int i = LO; i < HI; i++) {
    const RowC& c = (i & 1) ? b : a;
    hp[HOFF + i] = pack2(geglu1(acc[2 * i], acc[2 * NPR + 2 * i], c.c0, c.c1, c.c2), geglu1(acc[2 * i + 1], acc[2 * NPR + 2 * i + 1], c.c0, c.c1, c.c2));
  }
}
__device__ __forceinline__ uint32_t mapa(uint32_t addr, uint32_t rank) { uint32_t r; asm("mapa.shared::cluster.u32 %0, %1, %2;" : "=r"(r) : "r"(addr), "r"(rank)); return r; }
__device__ __forceinline__ void peer_send(float (&acc)[64], uint32_t rbuf, uint32_t rbar) {
  #pragma unroll
  for (int jp = 0; jp < 4; jp++) {
    const int b = 32 + 8 * jp;
    asm volatile("st.async.weak.shared::cluster.mbarrier::complete_tx::bytes.v4.b32 [%0], {%1, %2, %3, %4}, [%5];"
      :: "r"(rbuf + jp * 512), "r"(pack2(acc[b], acc[b + 1])), "r"(pack2(acc[b + 2], acc[b + 3])), "r"(pack2(acc[b + 4], acc[b + 5])), "r"(pack2(acc[b + 6], acc[b + 7])), "r"(rbar) : "memory");
  }
}
template<bool ADD, bool LAST = false>
__device__ __forceinline__ void stage_out(float (&acc)[64], uint32_t lbuf, uint32_t stsm_base, uint32_t lhi, uint32_t l7, uint32_t bar, __nv_bfloat16* gp = nullptr, uint32_t lbase = 0) {
  uint32_t u[16];
  if constexpr (ADD) {
    #pragma unroll
    for (int jp = 0; jp < 4; jp++)
      asm volatile("ld.shared.v4.b32 {%0, %1, %2, %3}, [%4];" : "=r"(u[4 * jp]), "=r"(u[4 * jp + 1]), "=r"(u[4 * jp + 2]), "=r"(u[4 * jp + 3]) : "r"(lbuf + jp * 512) : "memory");
  }
  if constexpr (LAST) { wg_wait<0>(); fence_regs<0, 32>(acc); }
  #pragma unroll
  for (int i = 0; i < 16; i++) { const uint32_t v = pack2(acc[2 * i], acc[2 * i + 1]); u[i] = ADD ? hadd2(v, u[i]) : v; }
  if constexpr (LAST && LASTRED == 1) {
    const bool odd = l7 & 1;
    #pragma unroll
    for (int i = 0; i < 8; i++) {
      const int j = (i >> 1) * 2, h = i & 1;
      const uint32_t a = u[2 * j + h], b = u[2 * j + 2 + h];
      const uint32_t r = __shfl_xor_sync(0xffffffffu, odd ? a : b, 1);
      asm volatile("red.relaxed.gpu.global.add.noftz.v2.bf16x2 [%0], {%1, %2};" :: "l"(gp + j * 8 + h * 8 * DM), "r"(odd ? r : a), "r"(odd ? b : r) : "memory");
    }
    return;
  }
  if constexpr (LAST && LASTRED == 4) {
    #pragma unroll
    for (int i = 0; i < 16; i++)
      asm volatile("red.relaxed.gpu.global.add.noftz.bf16x2 [%0], %1;" :: "l"(gp + (i >> 1) * 8 + (i & 1) * 8 * DM), "r"(u[i]) : "memory");
    return;
  }
  __syncwarp();
  #pragma unroll
  for (int jj = 0; jj < 4; jj++) stsm4(stsm_base + (((2 * jj + lhi) ^ l7) << 4), u[4 * jj], u[4 * jj + 1], u[4 * jj + 2], u[4 * jj + 3]);
  if constexpr (LAST && LASTRED == 2) {
    __syncwarp();
    #pragma unroll
    for (int ii = 0; ii < 4; ii++) {
      asm volatile("ld.shared.v4.b32 {%0, %1, %2, %3}, [%4];" : "=r"(u[4 * ii]), "=r"(u[4 * ii + 1]), "=r"(u[4 * ii + 2]), "=r"(u[4 * ii + 3]) : "r"((lbase ^ ((ii & 1) << 6)) + ii * 512) : "memory");
    }
    #pragma unroll
    for (int ii = 0; ii < 4; ii++)
      asm volatile("red.relaxed.gpu.global.add.noftz.v4.bf16x2 [%0], {%1, %2, %3, %4};" :: "l"(gp + ii * 4 * DM), "r"(u[4 * ii]), "r"(u[4 * ii + 1]), "r"(u[4 * ii + 2]), "r"(u[4 * ii + 3]) : "memory");
    return;
  }
  warp_arrive(bar);
}
__device__ __forceinline__ void poll_cnt(const unsigned* cnt, unsigned base, unsigned n) {
  asm volatile("{\n.reg .pred p;\n.reg .u32 c, v;\nmov.u32 c, 0;\nKV_LOOP:\n"
    "ld.relaxed.gpu.global.u32 v, [%0];\nsub.u32 v, v, %1;\nsetp.ge.u32 p, v, %2;\n@p bra KV_DONE;\n"
    "nanosleep.u32 40;\nadd.u32 c, c, 1;\nsetp.lt.u32 p, c, 2000000;\n@p bra KV_LOOP;\ntrap;\nKV_DONE:\n}\n" :: "l"(cnt), "r"(base), "r"(n) : "memory");
}

__global__ void __cluster_dims__(2, 1, 1) __launch_bounds__(384, 1)
fused_kernel(const __grid_constant__ Maps maps, const __nv_bfloat16* __restrict__ x, __nv_bfloat16* __restrict__ out) {
  extern __shared__ __align__(1024) char smraw[];
  const uint32_t sb = smem_u32(smraw);
  const int tid = threadIdx.x;
  const int mt = blockIdx.x >> 3, s = blockIdx.x & 7;
  STAMP(0);
  #define XCOPY(K0, K1) { \
    const uint32_t r = (tid >> 3) & 3, c = tid & 7, row = (tid >> 5) * 16 + r; \
    const char* g = (const char*)x + (mt * 128 + row) * (DM * 2) + c * 16; \
    const uint32_t d = sb + OFF_X + row * 128 + ((c ^ r) << 4); \
    _Pragma("unroll") \
    for (int kb = K0; kb < K1; kb++) { \
      _Pragma("unroll") \
      for (int ii = 0; ii < 4; ii++) \
        asm volatile("cp.async.cg.shared.global" L2H " [%0], [%1], 16;" :: "r"((d ^ ((ii & 1) << 6)) + ii * 512 + kb * 16384), "l"(g + ii * 4 * DM * 2 + kb * 128) : "memory"); \
      asm volatile("cp.async.commit_group;" ::: "memory"); \
    } }
  if (tid < 256) XCOPY(0, NL0)
  if (tid == 288) prefetch_map(&maps.x);
  if (PFXB && tid >= 288 && tid < 288 + 32 * PFXB) {
    const char* pp = (const char*)x + (blockIdx.x * 16 + ((tid & 31) >> 1)) * (DM * 2) + ((tid >> 5) - 9 + NL) * 128 + (tid & 1) * 64;
    asm volatile("prefetch.global.L2 [%0];" :: "l"(pp) : "memory");
    asm volatile("prefetch.global.L2 [%0];" :: "l"(pp + 32) : "memory");
  }
  const uint32_t rank = s & 1;
  uint32_t budget = 0;
  const int w12 = __shfl_sync(0xffffffffu, tid >> 5, 0), wg = w12 >> 2;
  const int qc = 56 * s - 8 * (int)rank;
  if (wg == 2) asm volatile("setmaxnreg.dec.sync.aligned.u32 40;");
  if (w12 == 8) {
    if (elect_one()) {
      #pragma unroll
      for (int i = NL; i < 7; i++) mbar_init(sb + BAR_X + 8 * i, 1);
      mbar_init(sb + BAR_FULL, 1); mbar_init(sb + BAR_FULL + 8, 1);
      fence_async();
      STAMPW(14);
      #pragma unroll
      for (int i = NL; i < 7; i++) { mbar_expect_tx(sb + BAR_X + 8 * i, 16384); if (!MC) tma2d(sb + OFF_X + i * 16384, &maps.x, sb + BAR_X + 8 * i, i * 64, mt * 128); }
      if (MC) asm volatile("fence.mbarrier_init.release.cluster;" ::: "memory");
      #pragma unroll
      for (int t = 0; t < 2; t++) {
        mbar_expect_tx(sb + BAR_FULL + 8 * t, 16384);
        if (T01) continue;
        tma2d(sb + buf_off(t), &maps.g, sb + BAR_FULL + 8 * t, 224 * s + 32 * rank, t * 64);
        tma2d(sb + buf_off(t) + 8192, &maps.u, sb + BAR_FULL + 8 * t, 224 * s + 32 * rank, t * 64);
      }
      STAMPW(15);
    }
  }
  if (wg == 2) {
    const int warp = w12 - 8;
    STAMPW(40 + warp);
    if (warp != 0 && elect_one()) {
      if (warp == 1) {
        mbar_init(sb + BAR_XW, 8); mbar_init(sb + BAR_XW2, 8); mbar_init(sb + BAR_TW, 8);
        mbar_init(sb + BAR_KVP, 256); mbar_init(sb + BAR_RDY2, 2);
        #pragma unroll
        for (int i = 0; i < 8; i++) { mbar_init(sb + BAR_RDY + 8 * i, 1); mbar_init(sb + BAR_OW + 8 * i, 4); }
      } else {
        #pragma unroll
        for (int i = 0; i < 16; i++) mbar_init(sb + BAR_DAT + 8 * ((warp - 2) * 16 + i), 1);
      }
      asm volatile("fence.mbarrier_init.release.cluster;" ::: "memory");
    }
    __syncwarp();
    STAMPW(44 + warp);
    asm volatile("barrier.cluster.arrive.relaxed.aligned;" ::: "memory");
    if (MC && warp == 0) {
      asm volatile("barrier.cluster.wait.acquire.aligned;" ::: "memory");
      if (elect_one()) {
        STAMPW(16);
        #pragma unroll
        for (int i = NL; i < 7; i++)
          asm volatile("cp.async.bulk.tensor.2d.shared::cluster.global.mbarrier::complete_tx::bytes.multicast::cluster [%0], [%1, {%3, %4}], [%2], %5;"
            :: "r"(sb + OFF_X + i * 16384 + rank * 8192), "l"(&maps.x), "r"(sb + BAR_X + 8 * i), "r"(i * 64), "r"(mt * 128 + (int)rank * 64), "h"((uint16_t)3) : "memory");
      }
      __syncwarp();
    }
    asm volatile("bar.sync 5, 384;" ::: "memory");
    if (warp == 0) {
      STAMPW(48);
      {
        const int lane = lane_id(), t = lane + 34;
        mbar_expect_tx(sb + BAR_DAT + 8 * lane, 2048);
        mbar_expect_tx(sb + BAR_FULL + 8 * (lane + 2), lane >= 19 && lane < 26 ? 16384 - 1024 * rank : 16384);
        if (t < 39) mbar_expect_tx(sb + BAR_FULL + 8 * t, t == 34 ? 16384 : (t == 35 ? 57344 : (t == 36 ? 53248 : 73728)));
        __syncwarp();
      }
      if (!elect_one()) return;
      fence_async();
      #define FREED(T) asm volatile("barrier.sync %0, 96;" :: "n"(8 + ((T) & 7)) : "memory")
      const int ck = 64 * rank, cs = 64 * (rank ^ 1);
      const int f32 = 224 * s + 192 * (rank ^ 1), f64 = 224 * s + 32 * rank;
      if (T01 == 1) {
        #pragma unroll
        for (int t = 0; t < 2; t++) {
          tma2d(sb + buf_off(t), &maps.g, sb + BAR_FULL + 8 * t, f64, t * 64);
          tma2d(sb + buf_off(t) + 8192, &maps.u, sb + BAR_FULL + 8 * t, f64, t * 64);
        }
      }
      #pragma unroll 1
      for (int i = 1; i < 12; i++) prefetch_map(&maps.x + i);
      if (T01 == 2) {
        #pragma unroll
        for (int t = 0; t < 2; t++) {
          tma2d(sb + buf_off(t), &maps.g, sb + BAR_FULL + 8 * t, f64, t * 64);
          tma2d(sb + buf_off(t) + 8192, &maps.u, sb + BAR_FULL + 8 * t, f64, t * 64);
        }
      }
      mbar_wait(sb + (PW1));
      asm volatile("cp.async.bulk.prefetch.L2.global [%0], %1;" :: "l"(maps.w[2] + blockIdx.x * 9408), "r"(9408) : "memory");
      mbar_wait(sb + (PW2));
      #pragma unroll 1
      for (int t = 2; t < 7; t++) {
        const uint32_t fb = sb + BAR_FULL + 8 * t, dst = sb + OFF_SLOT + (t == 5 ? 2 : (t == 2 ? 1 : t)) * 16384;
        STAMPW(64 + t);
        tma2d(dst, &maps.qkv, fb, 448 + qc, t * 64);
        tma2d(dst + 8192, &maps.qkv, fb, 896 + qc, t * 64);
      }
      SFOR(t, 7, 35)
        constexpr int kr = (t % 7) * 64;
        const uint32_t fb = sb + BAR_FULL + 8 * t, dst = sb + buf_off(t);
        if constexpr (t == 20) asm volatile("barrier.sync 1, 96;" ::: "memory");
        else FREED(t < 12 ? t - 7 : (t < 20 ? t - 5 : t - 6));
        STAMPW(64 + t);
        if constexpr (t >= 21 && t < 28) {
          tma2d(dst, &maps.g32, fb, f32, kr);
          tma2d(dst + 4096, &maps.u32, fb, f32, kr);
          tma2d(dst + 8192, &maps.q32, fb, 56 * s + 24 * rank, kr);
          tma2d(dst + 12288, &maps.q32 + rank, fb, 56 * s + 32 * (rank ^ 1), kr);
        } else if constexpr (t < 7 + NG) {
          tma2d(dst, &maps.qkv, fb, 448 + qc, kr);
          tma2d(dst + 8192, &maps.qkv, fb, 896 + qc, kr);
        } else {
          tma2d(dst, &maps.g, fb, f64 + (t < 14 ? 0 : (t < 21 ? 64 : 128)), kr);
          tma2d(dst + 8192, &maps.u, fb, f64 + (t < 14 ? 0 : (t < 21 ? 64 : 128)), kr);
        }
      SEND
      SFOR(i, 0, 18)
        constexpr int t = ord_of(i);
        if constexpr (dep_of(i) != 0) FREED(dep_of(i));
        const uint32_t fb = sb + BAR_FULL + 8 * (t < 39 ? 35 : (t < 43 ? 36 : (t < 48 ? 37 : 38))), dst = sb + buf_off(t);
        STAMPW(64 + t);
        constexpr bool dir = t >= 40 && t < 43;
        constexpr int v = t < 40 ? t - 35 : t - 38, p = v >= 10 ? 2 : (v >= 5), st = dir ? 2 * (t - 40) : v - 5 * p;
        constexpr int sb2 = dir ? st + 1 : st;
        const int r0 = st == 0 ? 56 * s : (st == 1 ? f32 : f64 + 64 * (st - 2)), r1 = sb2 == 0 ? 56 * s : (sb2 == 1 ? f32 : f64 + 64 * (sb2 - 2));
        tma2d(dst, &maps.o - (st < 2 ? st : 2), fb, dir ? 384 : 128 * p + ck, r0);
        if constexpr (t != 42) tma2d(dst + (st == 1 ? 4096 : 8192), &maps.o - (sb2 < 2 ? sb2 : 2), fb, dir ? 384 : 128 * p + cs, r1);
      SEND
      STAMPW(1);
    } else {
      unsigned* cnt = &g_cnt[s * 32];
      unsigned* cnt2 = &g_cnt2[mt * 32];
      const int lane = lane_id();
      unsigned e = 0;
      if (lane == 0) { asm volatile("ld.relaxed.gpu.global.u32 %0, [%1];" : "=r"(e) : "l"(cnt) : "memory"); e >>= 4; }
      e = __shfl_sync(0xffffffffu, e, 0);
      const unsigned par = e & 1;
      asm volatile("barrier.cluster.wait.acquire.aligned;" ::: "memory");
      if (warp == 2) {
        mbar_wait(sb + BAR_FULL + 8 * 5);
        const uint4* src = (const uint4*)(x + (mt * 128 + s * 16) * DM) + lane;
        uint4* dst = (uint4*)(out + (mt * 128 + s * 16) * DM) + lane;
        #pragma unroll 1
        for (int b = 0; b < 4; b++) {
          uint4 v[7];
          #pragma unroll
          for (int i = 0; i < 7; i++) v[i] = __ldg(src + (b * 7 + i) * 32);
          #pragma unroll
          for (int i = 0; i < 7; i++) dst[(b * 7 + i) * 32] = v[i];
        }
        __syncwarp();
        if (lane == 0) asm volatile("red.release.gpu.global.add.u32 [%0], 1;" :: "l"(cnt2) : "memory");
      } else if (warp == 3) {
        mbar_wait(sb + BAR_XW); fence_async(); if (lane == 0) mbar_arrive(sb + BAR_XR);
        mbar_wait(sb + BAR_XW2); fence_async(); if (lane == 0) mbar_arrive(sb + BAR_XR2);
        mbar_wait(sb + BAR_TW); fence_async(); if (lane == 0) mbar_arrive(sb + BAR_TILES);
      } else if (mt == 0) {
        float4* z = (float4*)&g_kvsum[((par ^ 1u) * 8 + s) * KVN];
        #pragma unroll 1
        for (int i = 0; i < 21; i++) z[lane + 32 * i] = make_float4(0.f, 0.f, 0.f, 0.f);
      }
      const float* sum = &g_kvsum[(par * 8 + s) * KVN] + ((warp - 1) * 7 * 32 + lane) * 4;
      if (warp == 1 && lane == 0) asm volatile("st.shared.u32 [%0], %1;" :: "r"(sb + OFF_PAR), "r"(par) : "memory");
      if (warp == 1) {
        __syncwarp();
        if (lane == 0) mbar_arrive(sb + BAR_PAR);
        const uint32_t n = lane == 2 ? 9408 : (lane == 4 ? 3136 : 12544);
        const char* p = maps.w[lane < 5 ? lane : 0] + blockIdx.x * n;
        mbar_wait(sb + BAR_FULL + 8 * PFW);
        if (lane < (PFK ? 2 : 3)) asm volatile("cp.async.bulk.prefetch.L2.global [%0], %1;" :: "l"(p), "r"(n) : "memory");
        mbar_wait(sb + BAR_FULL + 8 * PFW2);
        if (lane == 3 || lane == 4) asm volatile("cp.async.bulk.prefetch.L2.global [%0], %1;" :: "l"(p), "r"(n) : "memory");
      }
      mbar_wait(sb + BAR_KVP);
      if (warp == 1) {
        STAMPW(2);
        if (lane == 0) asm volatile("red.release.gpu.global.add.u32 [%0], 1;" :: "l"(cnt) : "memory");
        STAMPW(3);
      } else {
        #pragma unroll
        for (int i = 0; i < 8; i++)
          asm volatile("st.shared.v4.u32 [%0], {%1, %1, %1, %1};" :: "r"(sb + OFF_KVB + ((warp - 2) * 256 + lane + 32 * i) * 16), "r"(0) : "memory");
      }
      asm volatile("bar.sync 3, 96;" ::: "memory");
      uint32_t bP = sb + OFF_KVB + (lane >> 2) * 144 + (lane & 3) * 4 + rank * 32 * 128, bM = bP - rank * 56 * 128;
      uint32_t bD = sb + OFF_KVB + (lane >> 3) * 2048 + (lane & 7) * 128 + ((7 ^ (lane & 7)) << 4) + rank * 32 * 128;
      asm volatile("" : "+r"(bP), "+r"(bM), "+r"(bD));
      if (lane == 0) poll_cnt(cnt, e << 4, 16);
      __syncwarp();
      if (warp == 1) STAMPW(4);
      float4 v[7];
      #pragma unroll
      for (int n = 0; n < 7; n++) {
        const float* p = sum + n * 128;
        asm volatile("ld.relaxed.gpu.global.v4.f32 {%0, %1, %2, %3}, [%4];" : "=f"(v[n].x), "=f"(v[n].y), "=f"(v[n].z), "=f"(v[n].w) : "l"(p) : "memory");
      }
      SFOR(w, 0, 3)
        if (warp == w + 1) {
          SFOR(n, 0, 7)
            constexpr int f = w * 7 + n, g = f >> 2, hb = g >= 2, j = f & 3, d = (g - hb) * 16;
            uint32_t a0 = ((d >= 24 ? bM : bP) ^ ((3 * hb + j) << 4)) + d * 128, a1 = ((d >= 16 ? bM : bP) ^ ((3 * hb + j) << 4)) + d * 128 + 1024;
            const bool cok = j == 3 * (1 - hb) ? (lane & 2) == 2 * hb : true;
            bool p0 = cok && g != 2, p1 = cok && (g == 1 ? lane < 16 : (g == 2 ? lane >= 16 : g != 4));
            if constexpr (f == 20) { a0 = bD + (lane >= 16 ? bM : bP) - bP; a1 = bD + 1024 + (lane >= 8 ? bM : bP) - bP; p0 = true; p1 = lane < 24; }
            asm volatile("{\n.reg .pred p, q;\nsetp.ne.u32 p, %4, 0;\nsetp.ne.u32 q, %5, 0;\n@p st.shared.u32 [%0], %2;\n@q st.shared.u32 [%1], %3;\n}"
              :: "r"(a0), "r"(a1), "r"(pack2(v[n].x, v[n].y)), "r"(pack2(v[n].z, v[n].w)), "r"((uint32_t)p0), "r"((uint32_t)p1) : "memory");
          SEND
        }
      SEND
      if (warp == 1) STAMPW(9);
      fence_async();
      __syncwarp();
      if (lane == 0) mbar_arrive(sb + BAR_KVB);
      if (warp == 1) STAMPW(5);
      if (warp < 3 && elect_one()) {
        poll_cnt(cnt2, e << 3, 8);
        if (LASTRED && warp == 1) { asm volatile("fence.acq_rel.gpu;" ::: "memory"); mbar_arrive(sb + BAR_FULL + 8 * 38); }
        asm volatile("fence.proxy.async;" ::: "memory");
        if (warp == 2) STAMPW(7);
        #pragma unroll 1
        for (int i = 0; i < NOUT; i++) {
          mbar_wait(sb + BAR_OW + (warp - 1) * 32 + i * 8);
          fence_async();
          const int p = (i + 3) & 3;
          asm volatile("cp.reduce.async.bulk.tensor.2d.global.shared::cta.add.tile.bulk_group [%0, {%2, %3}], [%1];"
            :: "l"(&maps.out), "r"(sb + OFF_X + (3 + p) * 16384 + (warp - 1) * 8192), "r"(128 * p + (i ? 64 * (int)rank : 0)), "r"(mt * 128 + (warp - 1) * 64) : "memory");
          if (warp == 2) STAMPW(20 + i);
        }
        asm volatile("cp.async.bulk.commit_group;" ::: "memory");
        asm volatile("cp.async.bulk.wait_group.read 0;" ::: "memory");
        if (warp == 2) STAMPW(12);
      }
    }
    return;
  }

  if (MC) asm volatile("barrier.cluster.arrive.relaxed.aligned;" ::: "memory");
  if (w12 != 0 && elect_one()) {
    if ((sb & 0xFFFFFFu) != SB) __trap();
    #pragma unroll
    for (int i = 0; i < 6; i++) {
      const int n = i == 0 ? (w12 == 6 ? 4 : 1 + (LASTRED && w12 == 7)) : (i == 1 ? (w12 == 2 ? 5 : 1 + (w12 == 3)) : (i == 4 ? 1 + (w12 == 2) : (i == 5 ? 1 + (w12 <= 2) : 1)));
      mbar_init(sb + BAR_FULL + 8 * (w12 * 6 - 4 + i), n);
    }
  }
  __syncwarp();
  XCOPY(NL0, NL)
  STAMP(40);
  if (!MC) asm volatile("barrier.cluster.arrive.relaxed.aligned;" ::: "memory");
  asm volatile("bar.sync 5, 384;" ::: "memory");
  STAMP(41);
  asm volatile("setmaxnreg.inc.sync.aligned.u32 232;");
  STAMP(42);
  const int lane = lane_id(), wl = w12 & 3, w8 = w12;
  const uint32_t is0 = (tid & 127) == 0;
  const uint32_t fb = sb + BAR_FULL;
  const uint32_t aoff = wg * 512;
  const uint32_t lrow = (lane & 7) + ((lane >> 3) & 1) * 8, lhi = lane >> 4, l7 = lane & 7;

  #define REL(T) do { if constexpr ((T) == 5 || (T) == 6) mbar_arrive_pred(sb + BAR_E56, is0); \
    else asm volatile("{\n.reg .pred p;\nsetp.eq.u32 p, %0, 0;\n@p bar.arrive %1, 96;\n}" :: "r"(wl), "n"(8 + ((T) & 7)) : "memory"); } while (0)
  float accA[64], accB[64];
  uint32_t hp[56];
  RowC ca, cb;
  float ra, rb, rla, rlb;
  uint32_t xr[112];
  float vA, vB, kvacc[20];
  uint32_t par;
  #define SQ_ACC(B0, B1) \
    _Pragma("unroll") \
    for (int b2 = B0; b2 < B1; b2++) { \
      uint32_t qa = 0, qb = 0; \
      _Pragma("unroll") \
      for (int i = 16 * b2; i < 16 * b2 + 16; i += 2) { qa = hfma2(xr[i], xr[i], qa); qb = hfma2(xr[i + 1], xr[i + 1], qb); } \
      vA += bf_lo(qa) + bf_hi(qa); vB += bf_lo(qb) + bf_hi(qb); \
    } \
    asm volatile("" : "+f"(vA), "+f"(vB) :: "memory");
  {
    float s0[4] = {0.f, 0.f, 0.f, 0.f}, s1[4] = {0.f, 0.f, 0.f, 0.f}, vs[4] = {0.f, 0.f, 0.f, 0.f};
    float tA, tB;
    uint32_t xrow = sb + OFF_X + (w8 * 16 + lrow) * 128 + ((lhi ^ l7) << 4);
    asm volatile("" : "+r"(xrow));
    #pragma unroll
    for (int kb = 0; kb < 7; kb++) {
      if (kb < NL) { cp_wait(NL - 1 - kb); __syncwarp(); } else mbar_wait(sb + BAR_X + 8 * kb);
      STAMP(32 + kb);
      #pragma unroll
      for (int kk = 0; kk < 4; kk++) {
        const int i = (kb * 4 + kk) * 4;
        ldsm4(xr[i], xr[i + 1], xr[i + 2], xr[i + 3], (xrow ^ (kk << 5)) + kb * 16384);
      }
      #pragma unroll
      for (int db = 0; db < 2; db++) {
        const int b = kb - 1 + db;
        if (db == 0 ? (kb == 0 || (ES && kb == NL)) : !(kb == 6 || (ES && kb == NL - 1))) continue;
        if (b == NP) { tA = s0[0] + s1[0]; tB = s0[2] + s1[2]; }
        #pragma unroll
        for (int kk = 0; kk < 4; kk++) {
          const int i = (b * 4 + kk) * 4;
          if (kk & 1) mma_rowsum(s1, xr[i], xr[i + 1], xr[i + 2], xr[i + 3]); else mma_rowsum(s0, xr[i], xr[i + 1], xr[i + 2], xr[i + 3]);
        }
        if (b < NP) {
          #pragma unroll
          for (int i = 0; i < 16; i++) {
            const float lo = bf_lo(xr[16 * b + i]), hi = bf_hi(xr[16 * b + i]);
            vs[i & 1] = fmaf(lo, lo, vs[i & 1]); vs[2 + (i & 1)] = fmaf(hi, hi, vs[2 + (i & 1)]);
          }
          asm volatile("" : "+f"(vs[0]), "+f"(vs[1]), "+f"(vs[2]), "+f"(vs[3]) :: "memory");
        }
      }
    }
    STAMP(1);
    const float sA = s0[0] + s1[0], sB = s0[2] + s1[2];
    const float meanA = sA * (1.0f / DM), meanB = sB * (1.0f / DM);
    uint32_t mA = pack2(meanA, meanA), mB = pack2(meanB, meanB);
    #pragma unroll
    for (int i = 0; i < 16; i++) xr[i] = hsub2(xr[i], (i & 1) ? mB : mA);
    SFOR(kb, 0, 7)
      budget = 0;
      mbar_wait(fb + 8 * kb);
      STAMP(64 + kb);
      wg_fence();
      SFOR(kk, 0, 4)
        constexpr int i = (kb * 4 + kk) * 4;
        if constexpr (kb < NG) wg_rs128<(kb | kk) != 0, dB128 + ((buf_off(kb) + kk * 2048) >> 4)>(accB, xr[i], xr[i + 1], xr[i + 2], xr[i + 3]);
        else wg_rs120<(kb != NG || kk != 0), dB128 + ((buf_off(kb) + kk * 2048) >> 4)>(accA, xr[i], xr[i + 1], xr[i + 2], xr[i + 3], rank);
      SEND
      wg_commit();
      #pragma unroll
      for (int kk = 0; kk < 4; kk++) {
        const int i = (kb * 4 + kk) * 4;
        stsm4((xrow ^ (kk << 5)) + kb * 16384, xr[i], xr[i + 1], xr[i + 2], xr[i + 3]);
      }
      if constexpr (kb == 4) warp_arrive(sb + BAR_XW);
      if constexpr (kb == 6) warp_arrive(sb + BAR_XW2);
      if constexpr (kb > 0) { wg_wait<1>(); REL(kb - 1); }
      if constexpr (kb + 1 >= NP && kb < 5) pin2(mA, mB);
      if constexpr (kb < 6) {
        #pragma unroll
        for (int i = 16 * (kb + 1); i < 16 * (kb + 2); i++) xr[i] = hsub2(xr[i], (i & 1) ? mB : mA);
      }
      if constexpr (kb == 0) {
        const float eA = meanA - bf_lo(mA), eB = meanB - bf_lo(mB);
        vA = vs[0] + vs[2] + 0.25f * (meanA * (64.f * NP * meanA - 2.f * tA) + eA * ((448.f - 64.f * NP) * (meanA + bf_lo(mA)) - 2.f * (sA - tA)));
        vB = vs[1] + vs[3] + 0.25f * (meanB * (64.f * NP * meanB - 2.f * tB) + eB * ((448.f - 64.f * NP) * (meanB + bf_lo(mB)) - 2.f * (sB - tB)));
        asm volatile("" : "+f"(vA), "+f"(vB) :: "memory");
      }
      if constexpr (kb + 1 >= NP && kb < 5) { SQ_ACC(kb + 1, kb + 2) }
      if constexpr (kb == 6) { SQ_ACC(6, 7) }
    SEND
  }
  STAMP(2);
  #define SS_ISSUE(ACC, T) \
    SFOR(kk, 0, 4) \
      wg_ss128<(kb | kk) != 0, dA + ((kb * 16384 + kk * 32) >> 4), dB128 + ((buf_off(T) + kk * 2048) >> 4)>(ACC, aoff); \
    SEND
  {
    const uint32_t lane1 = lane_id(), trow = sb + OFF_SLOT + (2 + 4 * wg) * 16384 + (wl * 16 + (lane1 & 15)) * 128 + (((lane1 >> 4) ^ (lane1 & 7)) << 4);
    uint32_t pk[14], vv[14];
    #define PHI_K(LO, HI) _Pragma("unroll") \
      for (int i = LO; i < HI; i++) pk[i] = (i & 1) ? phi2(accA[2 * i], accA[2 * i + 1], rb, rlb) : phi2(accA[2 * i], accA[2 * i + 1], ra, rla);
    #define SCALE_V(LO, HI) _Pragma("unroll") \
      for (int i = LO; i < HI; i++) { const float r = (i & 1) ? rb : ra; vv[i] = pack2(accA[32 + 2 * i] * r, accA[33 + 2 * i] * r); }
    #define ST_K(J) stsm4(trow ^ ((J) << 5), pk[4 * (J)], pk[4 * (J) + 1], pk[4 * (J) + 2], pk[4 * (J) + 3]);
    #define ST_V(J) stsm4((trow ^ ((J) << 5)) + 8192, vv[4 * (J)], vv[4 * (J) + 1], vv[4 * (J) + 2], vv[4 * (J) + 3]);
    SFOR(kb, 0, 7)
      constexpr int t = 7 + kb;
      mbar_wait(fb + 8 * t);
      STAMP(64 + t);
      wg_fence();
      if constexpr (kb < NG) {
        SFOR(kk, 0, 4)
          wg_ss120b<1, dA + ((kb * 16384 + kk * 32) >> 4), dB128 + ((buf_off(t) + kk * 2048) >> 4)>(accA, aoff, rank);
        SEND
      } else {
        SS_ISSUE(accB, t)
      }
      wg_commit();
      if constexpr (kb == 4) {
        PHI_K(4, 8) SCALE_V(2, 4) ST_K(1) ST_V(0)
      } else if constexpr (kb == 5) {
        PHI_K(8, 12) SCALE_V(4, 8) ST_K(2) ST_V(1)
      } else if constexpr (kb == 6) {
        asm volatile("ld.shared.u32 %0, [%1];" : "=r"(par) : "r"(sb + OFF_PAR) : "memory");
        PHI_K(12, 14) SCALE_V(8, 14) ST_V(2)
        const uint32_t one = (lane1 & 3) == 0 ? 0x00003F80u : 0u;
        stsm4((trow ^ 96) + 8192, vv[12], vv[13], one, one);
        stsm4(trow ^ 96, pk[12], pk[13], 0u, 0u);
        warp_arrive(sb + BAR_TW);
      }
      wg_wait<1>();
      if constexpr (kb == 2) fence_regs<0, 60>(accA);
      REL(t - 1);
      if constexpr (kb == 0) {
        vA += __shfl_xor_sync(0xffffffffu, vA, 1); vB += __shfl_xor_sync(0xffffffffu, vB, 1);
        vA += __shfl_xor_sync(0xffffffffu, vA, 2); vB += __shfl_xor_sync(0xffffffffu, vB, 2);
        vA = fmaxf(vA * (1.0f / DM), 0.f); vB = fmaxf(vB * (1.0f / DM), 0.f);
        ra = rcp(bf_round(sqrt_approx(bf_round(bf_round(vA) + 1e-5f))));
        rb = rcp(bf_round(sqrt_approx(bf_round(bf_round(vB) + 1e-5f))));
        ca.c0 = 0.7978845608f * ra; ca.c1 = 0.0356774081f * ra * ra * ra; ca.c2 = 0.5f * ra * ra;
        cb.c0 = 0.7978845608f * rb; cb.c1 = 0.0356774081f * rb * rb * rb; cb.c2 = 0.5f * rb * rb;
        rla = ra * 1.4426950409f; rlb = rb * 1.4426950409f;
        asm volatile("" : "+f"(ra), "+f"(rb), "+f"(rla), "+f"(rlb), "+f"(ca.c0), "+f"(ca.c1), "+f"(ca.c2), "+f"(cb.c0), "+f"(cb.c1), "+f"(cb.c2) :: "memory");
      } else if constexpr (kb == 2) {
        PHI_K(0, 4) SCALE_V(0, 2) ST_K(0)
        asm volatile("" : "+r"(vv[0]), "+r"(vv[1]) :: "memory");
      }
    SEND
  }
  STAMP(3);
  #define EPI16(ACC, HOFF) \
    if constexpr (kb == 0) geglu_slice<0, 3, 16, HOFF>(hp, ACC, ca, cb); \
    else if constexpr (kb >= 2 && kb < 5) geglu_slice<3 * kb - 3, 3 * kb, 16, HOFF>(hp, ACC, ca, cb); \
    else if constexpr (kb >= 5) geglu_slice<2 * kb + 2, 2 * kb + 4, 16, HOFF>(hp, ACC, ca, cb);
  SFOR(kb, 0, 7)
    constexpr int t = 14 + kb;
    mbar_wait(fb + 8 * t);
    STAMP(64 + t);
    wg_fence();
    if constexpr (kb == 1) {
      SFOR(kk, 0, 8)
        constexpr uint64_t da = dB128 + ((OFF_SLOT + 2 * 16384) >> 4) + (kk >> 2) * 4096 + (kk & 3) * 128;
        wg_ss40t<kk != 0, da, da + 512>(kvacc, wg * 3);
      SEND
      wg_commit();
      wg_wait<1>();
      REL(14);
      wg_fence();
    }
    SS_ISSUE(accA, t)
    wg_commit();
    wg_wait<1>();
    if constexpr (kb == 1) {
      asm volatile("{\n.reg .pred p;\nsetp.eq.u32 p, %0, 0;\n@p bar.arrive 1, 96;\n}" :: "r"(wl) : "memory");
      fence_regs<0, 20>(kvacc);
      const int lane = lane_id(), q = lane & 3;
      float* sum = &g_kvsum[(par * 8 + s) * KVN];
      const uint32_t okw = wg == 0 ? (wl < 2) : (wl * 32 + lane >= 48), oke = okw && (q >> 1) == wg;
      const bool hb0 = wl >= 2, hb1 = wl * 16 + (lane >> 2) >= 20;
      float* p = sum + ((wg == 0 ? wl * 4 : 4 + wl * 4) * 32 + lane) * 4;
      #pragma unroll
      for (int j = 0; j < 4; j++)
        asm volatile("{\n.reg .pred p;\nsetp.ne.u32 p, %5, 0;\n@p red.relaxed.gpu.global.add.v4.f32 [%0], {%1, %2, %3, %4};\n}"
          :: "l"(p + j * 128), "f"(kvacc[4 * j]), "f"(kvacc[4 * j + 1]), "f"(kvacc[4 * j + 2]), "f"(kvacc[4 * j + 3]),
             "r"(j == 0 ? (wg ? oke : okw) : (j == 3 ? (wg ? okw : oke) : okw)) : "memory");
      asm volatile("{\n.reg .pred p;\nsetp.ne.u32 p, %5, 0;\n@p red.relaxed.gpu.global.add.v4.f32 [%0], {%1, %2, %3, %4};\n}"
        :: "l"(sum + (20 * 32 + wl * 8 + (lane >> 2)) * 4), "f"(hb0 ? 0.f : kvacc[16]), "f"(hb0 ? kvacc[16] : 0.f), "f"(hb1 ? 0.f : kvacc[18]), "f"(hb1 ? kvacc[18] : 0.f), "r"((uint32_t)(wg == 1 && q == 0)) : "memory");
      mbar_arrive(sb + BAR_KVP);
    } else {
      if constexpr (kb == 0) fence_regs<0, 64>(accB);
      REL(t - 1);
      geglu_slice<kb == 0 ? 0 : (kb == 2 ? 3 : 3 * kb - 5), kb == 0 ? 3 : 3 * kb - 2, 16, 8>(hp, accB, ca, cb);
    }
  SEND
  STAMP(4);
  SFOR(kb, 0, 7)
    constexpr int t = 21 + kb;
    mbar_wait(fb + 8 * t);
    STAMP(64 + t);
    wg_fence();
    SFOR(kk, 0, 4)
      wg_ss120<(kb | kk) != 0, dA + ((kb * 16384 + kk * 32) >> 4), dB64 + ((buf_off(t) + kk * 1024) >> 4)>(accB, aoff);
    SEND
    wg_commit();
    wg_wait<1>();
    if constexpr (kb == 0) fence_regs<0, 64>(accA);
    REL(t - 1);
    EPI16(accA, 24)
  SEND
  STAMP(5);
  uint32_t op[14];
  {
    uint32_t pq[14];
    SFOR(kb, 0, 7)
      constexpr int t = 28 + kb;
      mbar_wait(fb + 8 * t);
      if constexpr (kb == 6) asm volatile("{\n.reg .pred p;\nsetp.eq.u32 p, %0, 0;\n@p bar.sync 6, 256;\n}" :: "r"(wg) : "memory");
      STAMP(64 + t);
      wg_fence();
      SS_ISSUE(accA, t)
      if constexpr (kb == 4) {
        SFOR(kk, 0, 3)
          wg_rs64h<kk != 0, dB128 + ((OFF_KVB + kk * 2048) >> 4)>(accB, pq[4 * kk], pq[4 * kk + 1], pq[4 * kk + 2], pq[4 * kk + 3]);
        SEND
        wg_rs64h<1, dB128 + ((OFF_KVB + 6144) >> 4)>(accB, pq[12], pq[13], 0u, 0u);
      }
      wg_commit();
      if constexpr (kb == 6) asm volatile("{\n.reg .pred p;\nsetp.ne.u32 p, %0, 0;\n@p bar.arrive 6, 256;\n}" :: "r"(wg) : "memory");
      wg_wait<1>();
      if constexpr (kb == 0) fence_regs<0, 60>(accB);
      REL(t - 1);
      constexpr int plo = kb == 0 ? 0 : 5 * kb - 5, phi_ = kb == 0 ? 5 : (kb == 1 ? 0 : 5 * kb);
      #pragma unroll
      for (int i = plo; i < phi_ && i < 14; i++)
        pq[i] = (i & 1) ? phi2(accB[32 + 2 * i], accB[33 + 2 * i], rb, rlb) : phi2(accB[32 + 2 * i], accB[33 + 2 * i], ra, rla);
      if constexpr (kb >= 3 && kb < 6) geglu_slice<kb == 3 ? 0 : 4 * kb - 15, kb == 5 ? 8 : 4 * kb - 11, 8, 0>(hp, accB, ca, cb);
      if constexpr (kb == 5) {
        fence_regs<32, 64>(accB);
        const int lane = lane_id(), q = lane & 3;
        float dn[4];
        #pragma unroll
        for (int i = 0; i < 4; i++) dn[i] = rcp(__shfl_sync(0xffffffffu, accB[60 + i], lane & ~3) + 1e-6f);
        #pragma unroll
        for (int i = 0; i < 14; i++) {
          const int j = i >> 1, hf = i & 1;
          const float dv = j < 3 ? dn[2 * hf] : (j > 3 ? dn[2 * hf + 1] : (q < 2 ? dn[2 * hf] : dn[2 * hf + 1]));
          op[i] = pack2(accB[32 + 2 * i] * dv, accB[33 + 2 * i] * dv);
        }
      }
    SEND
  }
  STAMP(6);
  uint32_t xb = w8;
  asm volatile("" : "+r"(xb));
  xb = sb + OFF_X + 3 * 16384 + xb * 2048;
  const uint32_t lane2 = lane_id(), lrow2 = lane2 & 15, lhi2 = lane2 >> 4, l72 = lane2 & 7;
  const uint32_t peer_xb = mapa(xb + lane2 * 16, rank ^ 1), peer_bar = mapa(sb + BAR_DAT + w8 * 32, rank ^ 1);
  const uint32_t owb = sb + BAR_OW + wg * 32;
  __nv_bfloat16* gp = nullptr; uint32_t lbase = 0;
  #define PP_WAIT() asm volatile("bar.sync %0, 256;" :: "r"(6 + wg) : "memory")
  #define PP_PASS() asm volatile("bar.arrive %0, 256;" :: "r"(7 - wg) : "memory")
  #define FULL(T) mbar_wait(fb + 8 * (T))
  #define G2_AB(WG, ACC, T, O, OH) \
    WG<0, (dB128 + ((buf_off(T) + (O)) >> 4))>(ACC, op[0], op[1], op[2], op[3]); \
    WG<1, (dB128 + ((buf_off(T) + (O) + 2048) >> 4))>(ACC, op[4], op[5], op[6], op[7]); \
    WG<1, (dB128 + ((buf_off(T) + (O) + 4096) >> 4))>(ACC, op[8], op[9], op[10], op[11]); \
    WG<1, (dB128 + ((buf_off(T) + (O) + 6144) >> 4))>(ACC, op[12], op[13], 0u, 0u); \
    WG<1, (dB128h + ((OH) >> 4))>(ACC, hp[0], hp[1], hp[2], hp[3]); \
    WG<1, (dB128h + (((OH) + 2048) >> 4))>(ACC, hp[4], hp[5], hp[6], hp[7]);
  #define G2_H(WG, ACC, OFF, H0, K0, K1) \
    SFOR(kk, K0, K1) \
      WG<1, (dB128 + (((OFF) + kk * 2048) >> 4))>(ACC, hp[(H0) + 4 * kk], hp[(H0) + 4 * kk + 1], hp[(H0) + 4 * kk + 2], hp[(H0) + 4 * kk + 3]); \
    SEND
  #define XSEND(ACC, P) peer_send(ACC, peer_xb + (P) * 16384, peer_bar + (P) * 8)
  #define XRECV(ACC, P) mbar_wait(sb + BAR_DAT + w8 * 32 + (P) * 8); STAMP(26 + (P)); \
    stage_out<true, (P) == 2>(ACC, xb + (P) * 16384 + lane2 * 16, xb + (P) * 16384 + lrow2 * 128, lhi2, l72, owb + 8 + (P) * 8, gp, lbase)
  #define PP_WAIT_IF(W) asm volatile("{\n.reg .pred p;\nsetp.eq.u32 p, %0, " #W ";\n@p bar.sync 6 + " #W ", 256;\n}" :: "r"(wg) : "memory")
  #define PP_PASS_IF(W) asm volatile("{\n.reg .pred p;\nsetp.eq.u32 p, %0, " #W ";\n@p bar.arrive 7 - " #W ", 256;\n}" :: "r"(wg) : "memory")
  #define BURST1(W) \
      FULL(35); \
      if (W == 1) PP_WAIT(); \
      STAMP(64 + 35); \
      wg_fence(); \
      G2_AB(wg_rs128, accB, 35, 0, buf_off(36)) \
      G2_H(wg_rs128, accB, buf_off(37), 8, 0, 4) \
      G2_H(wg_rs128, accB, buf_off(38), 24, 0, 3) \
      wg_commit(); \
      if (W == 0) PP_PASS(); \
      G2_H(wg_rs128, accB, buf_off(38), 24, 3, 4) \
      wg_commit(); \
      if (W == 1) FULL(36); \
      wg_wait<1>(); \
      STAMP(64 + 36); \
      REL(37);
  #define EPI4() \
      fence_regs<0, 64>(accA); \
      REL(34); \
      asm volatile("{\n.reg .pred p;\nelect.sync _|p, 0xffffffff;\n@p mbarrier.arrive.shared::cluster.b64 _, [%0];\n}" :: "r"(mapa(sb + BAR_RDY + w8 * 8, rank ^ 1)) : "memory"); \
      FULL(35); \
      geglu_slice<0, 16, 16, 40>(hp, accA, ca, cb); \
      STAMP(64 + 37);
  if (wg == 0) {
    BURST1(0)
    EPI4()
    FULL(36);
    PP_WAIT();
  } else {
    wg_wait<0>();
    EPI4()
    BURST1(1)
  }
  STAMP(64 + 38);
  wg_fence();
  G2_H(wg_rs128, accB, buf_off(39), 40, 0, 4)
  G2_AB(wg_rs64, accA, 40, 0, buf_off(40) + 8192)
  G2_H(wg_rs64, accA, buf_off(41), 8, 0, 8)
  G2_H(wg_rs64, accA, buf_off(42), 40, 0, 2)
  wg_commit();
  PP_PASS();
  G2_H(wg_rs64, accA, buf_off(42), 40, 2, 4)
  wg_commit();
  wg_wait<1>();
  fence_regs<0, 64>(accB);
  STAMP(64 + 39);
  REL(41);
  asm volatile("{\n.reg .pred p;\nsetp.ne.u32 p, %1, 0;\n@p mbarrier.arrive.shared::cluster.b64 _, [%0];\n}" :: "r"(mapa(sb + BAR_RDY2, rank ^ 1)), "r"(is0) : "memory");
  mbar_wait(sb + BAR_RDY + w8 * 8);
  XSEND(accB, 0);
  wg_wait<0>();
  fence_regs<0, 32>(accA);
  stage_out<false>(accA, 0, xb + 3 * 16384 + lrow2 * 128, lhi2, l72, owb);
  FULL(37);
  STAMP(64 + 40);
  PP_WAIT();
  STAMP(64 + 41);
  wg_fence();
  G2_AB(wg_rs128, accA, 43, 0, buf_off(44))
  G2_H(wg_rs128, accA, buf_off(45), 8, 0, 4)
  G2_H(wg_rs128, accA, buf_off(46), 24, 0, 4)
  G2_H(wg_rs128, accA, buf_off(47), 40, 0, 3)
  wg_commit();
  PP_PASS();
  G2_H(wg_rs128, accA, buf_off(47), 40, 3, 4)
  wg_commit();
  XRECV(accB, 0);
  mbar_wait(sb + BAR_RDY2);
  wg_wait<0>();
  fence_regs<0, 64>(accA);
  STAMP(64 + 42);
  XSEND(accA, 1);
  FULL(38);
  STAMP(64 + 43);
  PP_WAIT();
  STAMP(64 + 44);
  wg_fence();
  G2_AB(wg_rs64h, accB, 48, 8192, buf_off(49) + 4096)
  G2_H(wg_rs64h, accB, buf_off(50) + 8192, 8, 0, 4)
  G2_H(wg_rs64h, accB, buf_off(51) + 8192, 24, 0, 4)
  G2_H(wg_rs64h, accB, buf_off(52) + 8192, 40, 0, 2)
  wg_commit();
  PP_PASS();
  G2_H(wg_rs64h, accB, buf_off(52) + 8192, 40, 2, 4)
  wg_commit();
  XRECV(accA, 1);
  wg_wait<0>();
  fence_regs<32, 64>(accB);
  STAMP(64 + 45);
  XSEND(accB, 2);
  STAMP(64 + 46);
  PP_WAIT();
  STAMP(64 + 47);
  wg_fence();
  G2_AB(wg_rs64, accB, 48, 0, buf_off(49))
  G2_H(wg_rs64, accB, buf_off(50), 8, 0, 4)
  G2_H(wg_rs64, accB, buf_off(51), 24, 0, 4)
  G2_H(wg_rs64, accB, buf_off(52), 40, 0, 2)
  wg_commit();
  PP_PASS_IF(1);
  G2_H(wg_rs64, accB, buf_off(52), 40, 2, 4)
  wg_commit();
  {
    uint32_t l3 = lane_id(), w3 = w8;
    asm volatile("" : "+r"(l3), "+r"(w3));
    const uint32_t q3 = l3 & 3;
    if (LASTRED == 1) gp = out + (mt * 128 + w3 * 16 + (l3 >> 2)) * DM + 256 + 64 * rank + ((q3 & 1) ? 6 + 2 * q3 : 2 * q3);
    if (LASTRED == 4) gp = out + (mt * 128 + w3 * 16 + (l3 >> 2)) * DM + 256 + 64 * rank + 2 * q3;
    if (LASTRED == 2) { gp = out + (mt * 128 + w3 * 16 + (l3 >> 3)) * DM + 256 + 64 * rank + 8 * (l3 & 7); lbase = xb + 2 * 16384 + (l3 >> 3) * 128 + (((l3 & 7) ^ (l3 >> 3)) << 4); }
  }
  XRECV(accB, 2);
  STAMP(12);
}

typedef CUresult (*PFN_enc)(CUtensorMap*, CUtensorMapDataType, cuuint32_t, void*, const cuuint64_t*, const cuuint64_t*, const cuuint32_t*, const cuuint32_t*,
                            CUtensorMapInterleave, CUtensorMapSwizzle, CUtensorMapL2promotion, CUtensorMapFloatOOBfill);
void enc2d(PFN_enc enc, CUtensorMap* m, const void* base, uint64_t inner, uint64_t outer, uint32_t bi, uint32_t bo, CUtensorMapSwizzle sw) {
  cuuint64_t dims[2] = {inner, outer}; cuuint64_t strides[1] = {inner * 2};
  cuuint32_t box[2] = {bi, bo}; cuuint32_t es[2] = {1, 1};
  enc(m, CU_TENSOR_MAP_DATA_TYPE_BFLOAT16, 2, const_cast<void*>(base), dims, strides, box, es, CU_TENSOR_MAP_INTERLEAVE_NONE, sw,
      CU_TENSOR_MAP_L2_PROMOTION_L2_128B, CU_TENSOR_MAP_FLOAT_OOB_FILL_NONE);
}

}

extern "C" void kernel_launch(void* const* d_in, const int* in_sizes, int n_in, void* d_out, int out_size) {
  static PFN_enc enc = nullptr;
  if (!enc) {
    void* fn = nullptr; cudaDriverEntryPointQueryResult qr;
    cudaGetDriverEntryPoint("cuTensorMapEncodeTiled", &fn, cudaEnableDefault, &qr);
    enc = (PFN_enc)fn;
    cudaFuncSetAttribute(fused_kernel, cudaFuncAttributeMaxDynamicSharedMemorySize, SMEM_BYTES);
  }
  Maps mp;
  const CUtensorMapSwizzle S128 = CU_TENSOR_MAP_SWIZZLE_128B, S64 = CU_TENSOR_MAP_SWIZZLE_64B;
  enc2d(enc, &mp.x, d_in[0], 448, 2048, 64, MC ? 64 : 128, S128);
  enc2d(enc, &mp.qkv, d_in[1], 1344, 448, 64, 64, S128);
  enc2d(enc, &mp.g, d_in[4], 1792, 448, 64, 64, S128);
  enc2d(enc, &mp.u, d_in[5], 1792, 448, 64, 64, S128);
  enc2d(enc, &mp.q32, d_in[1], 1344, 448, 32, 64, S64);
  enc2d(enc, &mp.q24, d_in[1], 1344, 448, 24, 64, S64);
  enc2d(enc, &mp.g32, d_in[4], 1792, 448, 32, 64, S64);
  enc2d(enc, &mp.u32, d_in[5], 1792, 448, 32, 64, S64);
  enc2d(enc, &mp.d, d_in[6], 448, 1792, 64, 64, S128);
  enc2d(enc, &mp.d32, d_in[6], 448, 1792, 64, 32, S128);
  enc2d(enc, &mp.o, d_in[2], 448, 448, 64, 64, S128);
  enc2d(enc, &mp.out, d_out, 448, 2048, 64, 64, S128);
  mp.w[0] = (const char*)d_in[4]; mp.w[1] = (const char*)d_in[5]; mp.w[2] = (const char*)d_in[1]; mp.w[3] = (const char*)d_in[6]; mp.w[4] = (const char*)d_in[2];
  fused_kernel<<<128, 384, SMEM_BYTES>>>(mp, (const __nv_bfloat16*)d_in[0], (__nv_bfloat16*)d_out);
}
```
